```python
import torch

def _softmax(x, axis=-1):
    return torch.softmax(x, dim=axis)
def _gelu(x):
    return torch.nn.functional.gelu(x, approximate="tanh")
def _silu(x):
    return torch.nn.functional.silu(x)
def _sigmoid(x):
    return torch.sigmoid(x)
def _layernorm(x, axis=-1, eps=1e-5):
    m = x.mean(dim=axis, keepdim=True)
    v = x.var(dim=axis, keepdim=True, unbiased=False)
    return (x - m) / torch.sqrt(v + eps)
def _scatter_add(tgt, idx, src, axis=0):
    return tgt.clone().index_add_(axis, idx, src)
def _segment_sum(src, seg, n):
    out = torch.zeros((n,) + src.shape[1:], dtype=src.dtype)
    return out.index_add_(0, seg, src)
def _pad(x, pw):
    flat = tuple(v for pair in reversed(pw) for v in pair)
    return torch.nn.functional.pad(x, flat)

kernel_name = 'gated_mix__grouped_kv_mqa__geglu_ffn__prompt'

def setup_inputs():

    _w = (lambda a: (lambda t: t.to(torch.bfloat16) if t.is_floating_point() else t)(torch.as_tensor(a)))
    def _A_setup():
        B, S, D, H = 1, 2048, 512, 32
        Dh = D // H
        return {
            "x": _w((lambda *s: torch.randn(*s, dtype=torch.bfloat16) * 0.05)(B, S, D)),
            "wq": _w((lambda *s: torch.randn(*s, dtype=torch.bfloat16) * 0.8)(D, H * Dh)),
            "wk": _w((lambda *s: torch.randn(*s, dtype=torch.bfloat16) * 0.8)(D, Dh)),
            "wv": _w((lambda *s: torch.randn(*s, dtype=torch.bfloat16) * 0.05)(D, Dh)),
            "wo": _w((lambda *s: torch.randn(*s, dtype=torch.bfloat16) * 0.05)(H * Dh, D)),
        }
    _A_in = _A_setup()

    def _B_setup():
        B, S, D, F = 1, 2048, 512, 1792
        return {
            "x": _w((lambda *s: torch.randn(*s, dtype=torch.bfloat16) * 0.05)(B, S, D)),
            "w_gate": _w((lambda *s: torch.randn(*s, dtype=torch.bfloat16) * 0.05)(D, F)),
            "w_up": _w((lambda *s: torch.randn(*s, dtype=torch.bfloat16) * 0.05)(D, F)),
            "w_down": _w((lambda *s: torch.randn(*s, dtype=torch.bfloat16) * 0.05)(F, D)),
        }
    _B_in = _B_setup()

    return {
        "A_x": _A_in["x"],
        "A_wq": _A_in["wq"],
        "A_wk": _A_in["wk"],
        "A_wv": _A_in["wv"],
        "A_wo": _A_in["wo"],
        "B_x": _B_in["x"],
        "B_w_gate": _B_in["w_gate"],
        "B_w_up": _B_in["w_up"],
        "B_w_down": _B_in["w_down"],
        "gate_w": _w((lambda *s: torch.randn(*s, dtype=torch.bfloat16) * 0.05)(512) * 16.0),
    }

def reference(A_x, A_wq, A_wk, A_wv, A_wo, B_x, B_w_gate, B_w_up, B_w_down, gate_w):
    def _A_ref(x, wq, wk, wv, wo):
        B, S, D = x.shape
        H = 32
        Dh = D // H
        q = (lambda x, *d: x.permute(*d))((x @ wq).reshape(B, S, H, Dh), 0, 2, 1, 3)
        k = x @ wk
        v = x @ wv
        scores = torch.einsum("bhqd,bkd->bhqk", q, k) * (Dh ** -0.5)
        p = _softmax(scores, axis=-1)
        o = torch.einsum("bhqk,bkd->bhqd", p, v)
        return (lambda x, *d: x.permute(*d))(o, 0, 2, 1, 3).reshape(B, S, H * Dh) @ wo

    def _B_ref(x, w_gate, w_up, w_down):
        return (_gelu(x @ w_gate) * (x @ w_up)) @ w_down

    x = A_x
    g = _sigmoid((x * gate_w).sum(-1, keepdims=True))
    a = _A_ref(x, A_wq, A_wk, A_wv, A_wo)
    b = _B_ref(x, B_w_gate, B_w_up, B_w_down)
    return g * a + (1 - g) * b
```

```cpp
#include <cuda_runtime.h>
#include <cuda_bf16.h>
#include <cuda.h>
#include <stdint.h>

#define POLYMASK 0x5555
#define REG_ATT 160
#define REG_GEMM 160
#define REG_PROD 32
#define FORCE_SLOW 0

namespace {

constexpr int S_ = 2048, D_ = 512, F_ = 1792;

constexpr uint32_t X_OFF = 0;
constexpr uint32_t W_OFF = 131072;
constexpr uint32_t KV_OFF = 196608;
constexpr uint32_t ONES_OFF = 229376;
constexpr uint32_t GW_OFF = 229888;
constexpr uint32_t G_OFF = 231040;
constexpr uint32_t MISC_OFF = 231552;
constexpr uint32_t BAR_OFF = 231616;
constexpr uint32_t B_XFULL = BAR_OFF;
constexpr uint32_t B_WKV = B_XFULL + 128;
constexpr uint32_t B_GREADY = B_WKV + 8;
constexpr uint32_t B_FFN1 = B_GREADY + 8;
constexpr uint32_t B_WFULL = B_FFN1 + 8;
constexpr uint32_t B_WEMPTY = B_WFULL + 32;
constexpr uint32_t B_KVFULL = B_WEMPTY + 32;
constexpr uint32_t B_KVEMPTY = B_KVFULL + 32;
constexpr uint32_t B_FFULL = B_KVEMPTY + 32;
constexpr uint32_t B_FEMPTY = B_FFULL + 64;
constexpr uint32_t B_WQ = B_FEMPTY + 64;
constexpr uint32_t SMEM_BYTES = B_WQ + 32;
constexpr uint32_t FST = 24576;
static_assert(SMEM_BYTES <= 232448, "smem");

constexpr int A_BYTES = 288 * 1024;
__device__ __align__(1024) uint8_t g_kv[32 * 4096];
__device__ __align__(1024) uint8_t g_a[32 * A_BYTES];
__device__ __align__(256) uint32_t g_flags[64 + 32 * 64];
__device__ uint32_t g_done;

#define EV(i)
struct Maps { CUtensorMap x, wq, wk, wv, wo, wg, wu, wd, out; };

__device__ __forceinline__ void wg_fence() { asm volatile("wgmma.fence.sync.aligned;" ::: "memory"); }
__device__ __forceinline__ void wg_commit() { asm volatile("wgmma.commit_group.sync.aligned;" ::: "memory"); }
template <int N> __device__ __forceinline__ void wg_wait() { asm volatile("wgmma.wait_group.sync.aligned %0;" ::"n"(N) : "memory"); }
template <int N> __device__ __forceinline__ void pin(float (&d)[N]) {
#pragma unroll
  for (int i = 0; i < N; i++) asm volatile("" : "+f"(d[i])::"memory");
}
template <int N> __device__ __forceinline__ void pinu(uint32_t (&d)[N]) {
#pragma unroll
  for (int i = 0; i < N; i++) asm volatile("" : "+r"(d[i])::"memory");
}
template <int N> __device__ __forceinline__ void zero(float (&d)[N]) {
#pragma unroll
  for (int i = 0; i < N; i++) d[i] = 0.f;
  pin(d);
}
__device__ __forceinline__ uint64_t mk64(uint32_t lo, uint32_t hi) { return ((uint64_t)hi << 32) | lo; }
__host__ __device__ constexpr uint32_t dhi(uint32_t sbo, uint32_t sw) { return (sbo >> 4) | (sw << 30); }
__device__ __forceinline__ uint32_t dlo(uint32_t addr, uint32_t lbo) { return (addr >> 4) | ((lbo >> 4) << 16); }

__device__ __forceinline__ void mbar_init(uint32_t b, uint32_t n) { asm volatile("mbarrier.init.shared::cta.b64 [%0], %1;" ::"r"(b), "r"(n) : "memory"); }
__device__ __forceinline__ void mbar_arrive(uint32_t b) { asm volatile("mbarrier.arrive.shared::cta.b64 _, [%0];" ::"r"(b) : "memory"); }
__device__ __forceinline__ void mbar_arrive2(uint32_t b) { asm volatile("mbarrier.arrive.shared::cta.b64 _, [%0], 2;" ::"r"(b) : "memory"); }
__device__ __forceinline__ void mbar_expect(uint32_t b, uint32_t bytes) { asm volatile("mbarrier.arrive.expect_tx.shared::cta.b64 _, [%0], %1;" ::"r"(b), "r"(bytes) : "memory"); }
__device__ __forceinline__ void mbar_wait(uint32_t b, uint32_t parity) {
  asm volatile(
      "{\n.reg .pred p;\n.reg .u32 c;\n"
      "mbarrier.try_wait.parity.shared::cta.b64 p, [%0], %1;\n"
      "@p bra DONE;\n"
      "mov.u32 c, 0;\n"
      "SPIN:\n"
      "mbarrier.try_wait.parity.shared::cta.b64 p, [%0], %1;\n"
      "@p bra DONE;\n"
      "add.u32 c, c, 1;\n"
      "setp.lt.u32 p, c, 0x100000;\n"
      "@p bra SPIN;\n"
      "trap;\n"
      "DONE:\n}\n" ::"r"(b), "r"(parity) : "memory");
}
__device__ __forceinline__ void tma2d(uint32_t dst, const CUtensorMap* m, int c0, int c1, uint32_t bar) {
  asm volatile("cp.async.bulk.tensor.2d.shared::cluster.global.mbarrier::complete_tx::bytes [%0], [%1, {%3, %4}], [%2];" ::"r"(dst), "l"(m), "r"(bar), "r"(c0), "r"(c1) : "memory");
}
__device__ __forceinline__ void bulk_ld(uint32_t dst, const void* src, uint32_t bytes, uint32_t bar) {
  asm volatile("cp.async.bulk.shared::cluster.global.mbarrier::complete_tx::bytes [%0], [%1], %2, [%3];" ::"r"(dst), "l"(src), "r"(bytes), "r"(bar) : "memory");
}
__device__ __forceinline__ void l2_prefetch(const void* src, uint32_t bytes) {
  asm volatile("cp.async.bulk.prefetch.L2.global [%0], %1;" ::"l"(src), "r"(bytes) : "memory");
}
__device__ __forceinline__ uint32_t ld_acq(const uint32_t* p) { uint32_t v; asm volatile("ld.acquire.gpu.global.u32 %0, [%1];" : "=r"(v) : "l"(p) : "memory"); return v; }
__device__ __forceinline__ void st_rel(uint32_t* p, uint32_t v) { asm volatile("st.release.gpu.global.u32 [%0], %1;" ::"l"(p), "r"(v) : "memory"); }
__device__ __forceinline__ void fence_async_all() { asm volatile("fence.proxy.async;" ::: "memory"); }
__device__ __forceinline__ void bar_sync(int id) { asm volatile("bar.sync %0, 128;" ::"r"(id) : "memory"); }
__device__ __forceinline__ uint32_t pack2(float lo, float hi) { uint32_t r; asm("cvt.rn.bf16x2.f32 %0, %1, %2;" : "=r"(r) : "f"(hi), "f"(lo)); return r; }
__device__ __forceinline__ float ex2(float a) { float r; asm("ex2.approx.ftz.f32 %0, %1;" : "=f"(r) : "f"(a)); return r; }
__device__ __forceinline__ float sqsum2(uint32_t p) { float a = __uint_as_float(p << 16), b = __uint_as_float(p & 0xffff0000u); return fmaf(a, a, b * b); }
__device__ __forceinline__ void stg32(void* p, uint32_t v) { asm volatile("st.global.u32 [%0], %1;" ::"l"(p), "r"(v) : "memory"); }
__device__ __forceinline__ void sts32(uint32_t a, uint32_t v) { asm volatile("st.shared.u32 [%0], %1;" ::"r"(a), "r"(v) : "memory"); }
__device__ __forceinline__ uint32_t lds32(uint32_t a) { uint32_t v; asm volatile("ld.shared.u32 %0, [%1];" : "=r"(v) : "r"(a) : "memory"); return v; }

__device__ __forceinline__ void mma_qk(float (&d)[32], const uint32_t (&a)[4], uint64_t b) {
  asm volatile("{\n.reg .pred p;\nsetp.ne.b32 p, 0, 0;\n"
    "wgmma.mma_async.sync.aligned.m64n64k16.f32.bf16.bf16 {%0,%1,%2,%3,%4,%5,%6,%7,%8,%9,%10,%11,%12,%13,%14,%15,%16,%17,%18,%19,%20,%21,%22,%23,%24,%25,%26,%27,%28,%29,%30,%31}, {%32,%33,%34,%35}, %36, p, 1, 1, 0;\n}\n"
    : "=f"(d[0]),"=f"(d[1]),"=f"(d[2]),"=f"(d[3]),"=f"(d[4]),"=f"(d[5]),"=f"(d[6]),"=f"(d[7]),"=f"(d[8]),"=f"(d[9]),"=f"(d[10]),"=f"(d[11]),"=f"(d[12]),"=f"(d[13]),"=f"(d[14]),"=f"(d[15]),"=f"(d[16]),"=f"(d[17]),"=f"(d[18]),"=f"(d[19]),"=f"(d[20]),"=f"(d[21]),"=f"(d[22]),"=f"(d[23]),"=f"(d[24]),"=f"(d[25]),"=f"(d[26]),"=f"(d[27]),"=f"(d[28]),"=f"(d[29]),"=f"(d[30]),"=f"(d[31]) : "r"(a[0]),"r"(a[1]),"r"(a[2]),"r"(a[3]),"l"(b));
}
__device__ __forceinline__ void mma_pv(float (&d)[12], const uint32_t (&a)[4], uint64_t b) {
  asm volatile("{\n.reg .pred p;\nsetp.ne.b32 p, 1, 0;\n"
    "wgmma.mma_async.sync.aligned.m64n24k16.f32.bf16.bf16 {%0,%1,%2,%3,%4,%5,%6,%7,%8,%9,%10,%11}, {%12,%13,%14,%15}, %16, p, 1, 1, 1;\n}\n"
    : "+f"(d[0]),"+f"(d[1]),"+f"(d[2]),"+f"(d[3]),"+f"(d[4]),"+f"(d[5]),"+f"(d[6]),"+f"(d[7]),"+f"(d[8]),"+f"(d[9]),"+f"(d[10]),"+f"(d[11]) : "r"(a[0]),"r"(a[1]),"r"(a[2]),"r"(a[3]),"l"(b));
}
__device__ __forceinline__ void mma_ss_t128(float (&d)[64], uint64_t a, uint64_t b, int acc) {
  asm volatile("{\n.reg .pred p;\nsetp.ne.b32 p, %66, 0;\n"
    "wgmma.mma_async.sync.aligned.m64n128k16.f32.bf16.bf16 {%0,%1,%2,%3,%4,%5,%6,%7,%8,%9,%10,%11,%12,%13,%14,%15,%16,%17,%18,%19,%20,%21,%22,%23,%24,%25,%26,%27,%28,%29,%30,%31,%32,%33,%34,%35,%36,%37,%38,%39,%40,%41,%42,%43,%44,%45,%46,%47,%48,%49,%50,%51,%52,%53,%54,%55,%56,%57,%58,%59,%60,%61,%62,%63}, %64, %65, p, 1, 1, 0, 1;\n}\n"
    : "+f"(d[0]),"+f"(d[1]),"+f"(d[2]),"+f"(d[3]),"+f"(d[4]),"+f"(d[5]),"+f"(d[6]),"+f"(d[7]),"+f"(d[8]),"+f"(d[9]),"+f"(d[10]),"+f"(d[11]),"+f"(d[12]),"+f"(d[13]),"+f"(d[14]),"+f"(d[15]),"+f"(d[16]),"+f"(d[17]),"+f"(d[18]),"+f"(d[19]),"+f"(d[20]),"+f"(d[21]),"+f"(d[22]),"+f"(d[23]),"+f"(d[24]),"+f"(d[25]),"+f"(d[26]),"+f"(d[27]),"+f"(d[28]),"+f"(d[29]),"+f"(d[30]),"+f"(d[31]),"+f"(d[32]),"+f"(d[33]),"+f"(d[34]),"+f"(d[35]),"+f"(d[36]),"+f"(d[37]),"+f"(d[38]),"+f"(d[39]),"+f"(d[40]),"+f"(d[41]),"+f"(d[42]),"+f"(d[43]),"+f"(d[44]),"+f"(d[45]),"+f"(d[46]),"+f"(d[47]),"+f"(d[48]),"+f"(d[49]),"+f"(d[50]),"+f"(d[51]),"+f"(d[52]),"+f"(d[53]),"+f"(d[54]),"+f"(d[55]),"+f"(d[56]),"+f"(d[57]),"+f"(d[58]),"+f"(d[59]),"+f"(d[60]),"+f"(d[61]),"+f"(d[62]),"+f"(d[63]) : "l"(a),"l"(b),"r"(acc));
}
__device__ __forceinline__ void mma_ss_t64(float (&d)[32], uint64_t a, uint64_t b, int acc) {
  asm volatile("{\n.reg .pred p;\nsetp.ne.b32 p, %34, 0;\n"
    "wgmma.mma_async.sync.aligned.m64n64k16.f32.bf16.bf16 {%0,%1,%2,%3,%4,%5,%6,%7,%8,%9,%10,%11,%12,%13,%14,%15,%16,%17,%18,%19,%20,%21,%22,%23,%24,%25,%26,%27,%28,%29,%30,%31}, %32, %33, p, 1, 1, 0, 1;\n}\n"
    : "+f"(d[0]),"+f"(d[1]),"+f"(d[2]),"+f"(d[3]),"+f"(d[4]),"+f"(d[5]),"+f"(d[6]),"+f"(d[7]),"+f"(d[8]),"+f"(d[9]),"+f"(d[10]),"+f"(d[11]),"+f"(d[12]),"+f"(d[13]),"+f"(d[14]),"+f"(d[15]),"+f"(d[16]),"+f"(d[17]),"+f"(d[18]),"+f"(d[19]),"+f"(d[20]),"+f"(d[21]),"+f"(d[22]),"+f"(d[23]),"+f"(d[24]),"+f"(d[25]),"+f"(d[26]),"+f"(d[27]),"+f"(d[28]),"+f"(d[29]),"+f"(d[30]),"+f"(d[31]) : "l"(a),"l"(b),"r"(acc));
}
__device__ __forceinline__ void mma_ss_t16(float (&d)[8], uint64_t a, uint64_t b, int acc) {
  asm volatile("{\n.reg .pred p;\nsetp.ne.b32 p, %10, 0;\n"
    "wgmma.mma_async.sync.aligned.m64n16k16.f32.bf16.bf16 {%0,%1,%2,%3,%4,%5,%6,%7}, %8, %9, p, 1, 1, 0, 1;\n}\n"
    : "+f"(d[0]),"+f"(d[1]),"+f"(d[2]),"+f"(d[3]),"+f"(d[4]),"+f"(d[5]),"+f"(d[6]),"+f"(d[7]) : "l"(a),"l"(b),"r"(acc));
}
__device__ __forceinline__ void mma_ss_n8(float (&d)[4], uint64_t a, uint64_t b, int acc) {
  asm volatile("{\n.reg .pred p;\nsetp.ne.b32 p, %6, 0;\n"
    "wgmma.mma_async.sync.aligned.m64n8k16.f32.bf16.bf16 {%0,%1,%2,%3}, %4, %5, p, 1, 1, 0, 0;\n}\n"
    : "+f"(d[0]),"+f"(d[1]),"+f"(d[2]),"+f"(d[3]) : "l"(a),"l"(b),"r"(acc));
}

__device__ __forceinline__ uint32_t exp2_pair_fma(float a, float b, uint32_t one) {
  float da = a + 8224.f, db = b + 8224.f;
  uint32_t u = __byte_perm(__float_as_uint(da), __float_as_uint(db), 0x5410);
  uint32_t g, t;
  asm("lop3.b32 %0, %1, 0x03FF03FF, %2, 0xEA;" : "=r"(g) : "r"(u), "r"(one));
  uint32_t un = u & 0xFC00FC00u;
  asm("fma.rn.f16x2 %0, %1, %2, %3;" : "=r"(t) : "r"(g), "r"(0x10F910F9u), "r"(0x836B836Bu));
  asm("fma.rn.f16x2 %0, %1, %2, %3;" : "=r"(t) : "r"(t), "r"(g), "r"(0x1B9D1B9Du));
  asm("fma.rn.f16x2 %0, %1, %2, %3;" : "=r"(t) : "r"(t), "r"(g), "r"(0x2F3A2F3Au));
  return t + (un >> 3);
}
template <int J> __device__ __forceinline__ void sm_unit(const float (&s)[32], uint32_t (&p)[4], uint32_t one) {
#pragma unroll
  for (int i = 0; i < 4; i++) {
    const int j = J * 4 + i;
    if ((POLYMASK >> j) & 1) p[i] = exp2_pair_fma(s[2 * j], s[2 * j + 1], one);
    else p[i] = pack2(ex2(s[2 * j]), ex2(s[2 * j + 1]));
  }
}

#define KD(lo) mk64((lo), dhi(256, 3))
#define VO(x) ((uint32_t)(x) - ((uint32_t)(x) << 16))

__device__ __forceinline__ void attn_fast(uint32_t sb, const uint32_t (&q0)[4], const uint32_t (&q1)[4], float (&o0)[12], float (&o1)[12], int lane, uint32_t one) {
  const uint32_t kvfull = sb + B_KVFULL, kvempty = sb + B_KVEMPTY;
  const uint32_t kbase = dlo(sb + KV_OFF, 16), vbase = dlo(sb + KV_OFF, ONES_OFF - KV_OFF);
  float s0[32], s1[32];
  zero(s0); zero(s1); zero(o0); zero(o1);
  {
    uint32_t p0[4]={0,0,0,0}; pinu(p0);
    uint32_t p1[4]={0,0,0,0}; pinu(p1);
    uint32_t p2[4]={0,0,0,0}; pinu(p2);
    uint32_t p3[4]={0,0,0,0}; pinu(p3);
    wg_fence(); mma_qk(s0, q0, KD(kbase)); wg_commit(); wg_wait<0>(); pin(s0);
    uint32_t vprev = vbase - VO(512);
#pragma unroll 1
    for (int it = 0; it < 8; it++) {
      const uint32_t sA = (it & 1) * 2, ph = (it >> 1) & 1, phn = ((it + 1) >> 1) & 1;
      const uint32_t kcur = kbase + sA * 512, knxt = kbase + (sA ^ 2) * 512, vcur = vbase + VO(sA * 512);
      wg_fence();
      mma_qk(s1,q1,KD(kcur+0));
      mma_pv(o1,p2,KD(vprev+VO(960)));
      mma_pv(o1,p3,KD(vprev+VO(992)));
      wg_commit();
      sm_unit<0>(s0,p0,one);
      sm_unit<1>(s0,p1,one);
      wg_fence();
      mma_pv(o0,p0,KD(vcur+VO(128)));
      mma_pv(o0,p1,KD(vcur+VO(160)));
      wg_commit();
      wg_wait<1>();
      if (lane==0 && it!=0) mbar_arrive(kvempty+8*((sA^2)+1));
      sm_unit<2>(s0,p2,one);
      sm_unit<3>(s0,p3,one);
      wg_fence();
      mma_qk(s0,q0,KD(kcur+256));
      mma_pv(o0,p2,KD(vcur+VO(192)));
      mma_pv(o0,p3,KD(vcur+VO(224)));
      wg_commit();
      wg_wait<1>(); pin(s1);
      sm_unit<0>(s1,p0,one);
      sm_unit<1>(s1,p1,one);
      wg_fence();
      mma_pv(o1,p0,KD(vcur+VO(128)));
      mma_pv(o1,p1,KD(vcur+VO(160)));
      wg_commit();
      wg_wait<1>();
      sm_unit<2>(s1,p2,one);
      sm_unit<3>(s1,p3,one);
      wg_fence();
      mma_qk(s1,q1,KD(kcur+256));
      mma_pv(o1,p2,KD(vcur+VO(192)));
      mma_pv(o1,p3,KD(vcur+VO(224)));
      wg_commit();
      wg_wait<1>(); pin(s0);
      sm_unit<0>(s0,p0,one);
      sm_unit<1>(s0,p1,one);
      wg_fence();
      mma_pv(o0,p0,KD(vcur+VO(384)));
      mma_pv(o0,p1,KD(vcur+VO(416)));
      wg_commit();
      wg_wait<1>();
      sm_unit<2>(s0,p2,one);
      sm_unit<3>(s0,p3,one);
      mbar_wait(kvfull+8*(sA+1), ph);
      wg_fence();
      mma_qk(s0,q0,KD(kcur+512));
      mma_pv(o0,p2,KD(vcur+VO(448)));
      mma_pv(o0,p3,KD(vcur+VO(480)));
      wg_commit();
      wg_wait<1>(); pin(s1);
      sm_unit<0>(s1,p0,one);
      sm_unit<1>(s1,p1,one);
      wg_fence();
      mma_pv(o1,p0,KD(vcur+VO(384)));
      mma_pv(o1,p1,KD(vcur+VO(416)));
      wg_commit();
      wg_wait<1>();
      sm_unit<2>(s1,p2,one);
      sm_unit<3>(s1,p3,one);
      wg_fence();
      mma_qk(s1,q1,KD(kcur+512));
      mma_pv(o1,p2,KD(vcur+VO(448)));
      mma_pv(o1,p3,KD(vcur+VO(480)));
      wg_commit();
      wg_wait<1>(); pin(s0);
      sm_unit<0>(s0,p0,one);
      sm_unit<1>(s0,p1,one);
      wg_fence();
      mma_pv(o0,p0,KD(vcur+VO(640)));
      mma_pv(o0,p1,KD(vcur+VO(672)));
      wg_commit();
      wg_wait<1>();
      if (lane==0) mbar_arrive(kvempty+8*sA);
      sm_unit<2>(s0,p2,one);
      sm_unit<3>(s0,p3,one);
      wg_fence();
      mma_qk(s0,q0,KD(kcur+768));
      mma_pv(o0,p2,KD(vcur+VO(704)));
      mma_pv(o0,p3,KD(vcur+VO(736)));
      wg_commit();
      wg_wait<1>(); pin(s1);
      sm_unit<0>(s1,p0,one);
      sm_unit<1>(s1,p1,one);
      wg_fence();
      mma_pv(o1,p0,KD(vcur+VO(640)));
      mma_pv(o1,p1,KD(vcur+VO(672)));
      wg_commit();
      wg_wait<1>();
      sm_unit<2>(s1,p2,one);
      sm_unit<3>(s1,p3,one);
      wg_fence();
      mma_qk(s1,q1,KD(kcur+768));
      mma_pv(o1,p2,KD(vcur+VO(704)));
      mma_pv(o1,p3,KD(vcur+VO(736)));
      wg_commit();
      wg_wait<1>(); pin(s0);
      sm_unit<0>(s0,p0,one);
      sm_unit<1>(s0,p1,one);
      wg_fence();
      mma_pv(o0,p0,KD(vcur+VO(896)));
      mma_pv(o0,p1,KD(vcur+VO(928)));
      wg_commit();
      wg_wait<1>();
      sm_unit<2>(s0,p2,one);
      sm_unit<3>(s0,p3,one);
      mbar_wait(kvfull+8*(sA^2), phn);
      wg_fence();
      mma_qk(s0,q0,KD(knxt));
      mma_pv(o0,p2,KD(vcur+VO(960)));
      mma_pv(o0,p3,KD(vcur+VO(992)));
      wg_commit();
      wg_wait<1>(); pin(s1);
      sm_unit<0>(s1,p0,one);
      sm_unit<1>(s1,p1,one);
      wg_fence();
      mma_pv(o1,p0,KD(vcur+VO(896)));
      mma_pv(o1,p1,KD(vcur+VO(928)));
      wg_commit();
      wg_wait<1>();
      sm_unit<2>(s1,p2,one);
      sm_unit<3>(s1,p3,one);
      wg_wait<0>(); pin(s0); pin(o0); pin(o1);
      vprev = vcur;
    }
    wg_fence();
    mma_pv(o1,p2,KD(vprev+VO(960)));
    mma_pv(o1,p3,KD(vprev+VO(992)));
    wg_commit(); wg_wait<0>(); pin(o0); pin(o1);
    if (lane == 0) mbar_arrive(kvempty + 8 * 3);
  }
}

__device__ __forceinline__ void slow_tile(const uint32_t (&q)[4], float (&o)[12], float& m0, float& m1, uint32_t kd, uint32_t vd) {
  float s[32];
  wg_fence(); mma_qk(s, q, KD(kd)); wg_commit(); wg_wait<0>(); pin(s);
  float a = m0, b = m1;
#pragma unroll
  for (int j = 0; j < 8; j++) { a = fmaxf(a, fmaxf(s[4 * j], s[4 * j + 1])); b = fmaxf(b, fmaxf(s[4 * j + 2], s[4 * j + 3])); }
  a = fmaxf(a, __shfl_xor_sync(~0u, a, 1)); a = fmaxf(a, __shfl_xor_sync(~0u, a, 2));
  b = fmaxf(b, __shfl_xor_sync(~0u, b, 1)); b = fmaxf(b, __shfl_xor_sync(~0u, b, 2));
  const float ca = ex2(m0 - a), cb = ex2(m1 - b);
  m0 = a; m1 = b;
#pragma unroll
  for (int j = 0; j < 3; j++) { o[4 * j] *= ca; o[4 * j + 1] *= ca; o[4 * j + 2] *= cb; o[4 * j + 3] *= cb; }
  uint32_t p[4][4];
#pragma unroll
  for (int j = 0; j < 8; j++) {
    p[j >> 1][(j & 1) * 2] = pack2(ex2(s[4 * j] - a), ex2(s[4 * j + 1] - a));
    p[j >> 1][(j & 1) * 2 + 1] = pack2(ex2(s[4 * j + 2] - b), ex2(s[4 * j + 3] - b));
  }
  pin(o);
  wg_fence();
#pragma unroll
  for (int j = 0; j < 4; j++) mma_pv(o, p[j], KD(vd + VO(128 + 32 * j)));
  wg_commit(); wg_wait<0>(); pin(o);
}
__device__ __forceinline__ void attn_slow(uint32_t sb, const uint32_t (&q0)[4], const uint32_t (&q1)[4], float (&o0)[12], float (&o1)[12], int lane) {
  const uint32_t kbase = dlo(sb + KV_OFF, 16), vbase = dlo(sb + KV_OFF, ONES_OFF - KV_OFF);
  zero(o0); zero(o1);
  float m00 = -INFINITY, m01 = -INFINITY, m10 = -INFINITY, m11 = -INFINITY;
#pragma unroll 1
  for (int c = 0; c < 32; c++) {
    const uint32_t off = (c & 7) * 256;
    slow_tile(q0, o0, m00, m01, kbase + off, vbase + VO(off));
    slow_tile(q1, o1, m10, m11, kbase + off, vbase + VO(off));
    if (c & 1) {
      if (lane == 0) mbar_arrive(sb + B_KVEMPTY + 8 * ((c >> 1) & 3));
      const int n = (c >> 1) + 1;
      mbar_wait(sb + B_KVFULL + 8 * (n & 3), (n >> 2) & 1);
    }
  }
}

__device__ __forceinline__ void store_o(const float (&o)[12], float g0, float g1, uint8_t* dst) {
  const float a = __fdividef(g0, o[8]), b = __fdividef(g1, o[10]);
  stg32(dst, pack2(o[0] * a, o[1] * a));
  stg32(dst + 128, pack2(o[2] * b, o[3] * b));
  stg32(dst + 1024, pack2(o[4] * a, o[5] * a));
  stg32(dst + 1152, pack2(o[6] * b, o[7] * b));
}

__device__ __forceinline__ float geglu(float x, float u, float c) {
  const float y = x * fmaf(x * x, 0.044715f * 0.7978845608028654f, 0.7978845608028654f);
  float t; asm("tanh.approx.f32 %0, %1;" : "=f"(t) : "f"(y));
  const float h = x * u * c;
  return fmaf(h, t, h);
}
__device__ __forceinline__ void store_h(const float (&d)[64], float c0, float c1, uint8_t* dst) {
#pragma unroll
  for (int j = 0; j < 8; j++) {
    stg32(dst + j * 1024, pack2(geglu(d[4 * j], d[32 + 4 * j], c0), geglu(d[4 * j + 1], d[33 + 4 * j], c0)));
    stg32(dst + j * 1024 + 128, pack2(geglu(d[4 * j + 2], d[34 + 4 * j], c1), geglu(d[4 * j + 3], d[35 + 4 * j], c1)));
  }
}

__device__ __forceinline__ int step_chunk(int s) {
  return s < 24 ? 7 * ((s & 7) >> 1) + 3 * (s & 1) + (s >> 3) : 7 * (s - 24) + 6;
}

__global__ void __launch_bounds__(512, 1)
fused_kernel(const __grid_constant__ Maps mp, const __nv_bfloat16* __restrict__ gate_w, const uint8_t* __restrict__ wd_raw, const uint8_t* __restrict__ wo_raw) {
  extern __shared__ __align__(1024) uint8_t smem[];
  const uint32_t sb = (uint32_t)__cvta_generic_to_shared(smem);
  const int tid = threadIdx.x, lane = tid & 31;
  const int warp = __shfl_sync(~0u, tid >> 5, 0);
  const int wg = warp >> 2, wq4 = warp & 3;
  const int tb = blockIdx.x >> 3, cg = blockIdx.x & 7;
  const int half = cg & 1;

  if (tid == 384) {
    if (sb & 1023) __trap();
    for (int i = 0; i < 16; i++) mbar_init(sb + B_XFULL + 8 * i, 1);
    mbar_init(sb + B_WKV, 1); mbar_init(sb + B_GREADY, 8); mbar_init(sb + B_FFN1, 4);
    for (int i = 0; i < 4; i++) { mbar_init(sb + B_WQ + 8 * i, 1); mbar_init(sb + B_WFULL + 8 * i, 1); mbar_init(sb + B_WEMPTY + 8 * i, 8); mbar_init(sb + B_KVFULL + 8 * i, 1); mbar_init(sb + B_KVEMPTY + 8 * i, 8); }
    for (int i = 0; i < 8; i++) { mbar_init(sb + B_FFULL + 8 * i, 2); mbar_init(sb + B_FEMPTY + 8 * i, 4); }
    asm volatile("fence.mbarrier_init.release.cluster;" ::: "memory");
    fence_async_all();
    if (cg < 4) {
      const CUtensorMap* m = cg < 2 ? &mp.wk : &mp.wv;
      mbar_expect(sb + B_WKV, 16384);
      tma2d(sb + KV_OFF, m, 0, 0, sb + B_WKV);
      tma2d(sb + KV_OFF + 8192, m, 0, 256, sb + B_WKV);
    }
    for (int hh = 0; hh < 2; hh++) {
      const int h = hh ^ half;
      for (int kc = 0; kc < 8; kc++) {
        const uint32_t b = sb + B_XFULL + 64 * h + 8 * kc;
        mbar_expect(b, 8192);
        tma2d(sb + X_OFF + kc * 16384 + h * 8192, &mp.x, kc * 64, tb * 128 + h * 64, b);
      }
      for (int s = 2 * hh; s < 2 * hh + 2; s++) {
        const uint32_t b = sb + B_WQ + 8 * s;
        mbar_expect(b, s == 3 ? 16384 + 1024 : 16384);
        tma2d(sb + W_OFF + s * 16384, &mp.wq, cg * 64, s * 128, b);
        tma2d(sb + W_OFF + s * 16384 + 8192, &mp.wq, cg * 64, s * 128 + 64, b);
        if (s == 3) bulk_ld(sb + GW_OFF, gate_w, 1024, b);
      }
    }
  }
  if (tid < 128) { sts32(sb + ONES_OFF + tid * 4, 0x3F803F80u); asm volatile("fence.proxy.async.shared::cta;" ::: "memory"); }
  __syncthreads();

  uint8_t* const a_tb = g_a + (size_t)(tb * 2) * A_BYTES;
  uint32_t* const fl_tb = g_flags + 64 + tb * 128;

  if (wg == 3) {
    asm volatile("setmaxnreg.dec.sync.aligned.u32 %0;" ::"n"(REG_PROD));
    if (wq4 == 0) {
      if (lane == 0) {
#pragma unroll 1
        for (int n = 4; n < 36; n++) {
          const int st = (n - 4) >> 3, kc = (n - 4) & 7, s = n & 3;
          const int hc = 7 * (cg >> 1) + (st < 3 ? 3 * half + st : 6);
          mbar_wait(sb + B_WEMPTY + 8 * s, ((n >> 2) & 1) ^ 1);
          const uint32_t b = sb + B_WFULL + 8 * s;
          mbar_expect(b, 16384);
          tma2d(sb + W_OFF + s * 16384, &mp.wg, hc * 64, kc * 64, b);
          tma2d(sb + W_OFF + s * 16384 + 8192, &mp.wu, hc * 64, kc * 64, b);
          if (n == 12) { l2_prefetch(wd_raw + blockIdx.x * 14336, 14336); l2_prefetch(wo_raw + blockIdx.x * 4096, 4096); }
        }
        mbar_wait(sb + B_FFN1, 0);
        const int col = (cg >> 1) * 128;
#pragma unroll 1
        for (int n = 0; n < 36; n++) {
          const int s = n & 7;
          mbar_wait(sb + B_FEMPTY + 8 * s, ((n >> 3) & 1) ^ 1);
          const uint32_t b = sb + B_FFULL + 8 * s, dst = sb + s * FST + 8192;
          mbar_expect(b, 16384);
          if (n < 28) {
            const int r = step_chunk(n) * 64;
            tma2d(dst, &mp.wd, col, r, b);
            tma2d(dst + 8192, &mp.wd, col + 64, r, b);
          } else {
            const int r = ((n - 28) & 3) * 128 + ((n - 28) >> 2) * 32;
            tma2d(dst, &mp.wo, col, r, b);
            tma2d(dst + 4096, &mp.wo, col, r + 64, b);
            tma2d(dst + 8192, &mp.wo, col + 64, r, b);
            tma2d(dst + 12288, &mp.wo, col + 64, r + 64, b);
          }
        }
      }
    } else if (wq4 == 1) {
      uint32_t fk, fv;
      for (int i = 0;; i++) {
        fk = ld_acq(g_flags + lane); fv = ld_acq(g_flags + 32 + lane);
        if (__all_sync(~0u, fk != 0 && fv != 0)) break;
        if (i > 0x100000) __trap();
      }
      fk = __reduce_max_sync(~0u, fk);
      if (lane == 0) {
        sts32(sb + MISC_OFF + 32, fk);
        fence_async_all();
#pragma unroll 1
        for (int n = 0; n < 33; n++) {
          const int s = n & 3;
          mbar_wait(sb + B_KVEMPTY + 8 * s, ((n >> 2) & 1) ^ 1);
          mbar_expect(sb + B_KVFULL + 8 * s, 8192);
          bulk_ld(sb + KV_OFF + s * 8192, g_kv + (n & 15) * 8192, 8192, sb + B_KVFULL + 8 * s);
        }
      }
    } else if (wq4 == 2) {
      mbar_wait(sb + B_FFN1, 0);
      const uint32_t* fl = fl_tb + half * 64;
      const uint8_t* src = a_tb + half * A_BYTES;
      uint32_t rh = 0, ro = 0;
#pragma unroll 1
      for (int n = 0; n < 36; n++) {
        const int ch = n < 28 ? step_chunk(n) : n;
        if (n < 28) {
          for (int i = 0; !((rh >> ch) & 1); i++) { rh = __ballot_sync(~0u, ld_acq(fl + lane) != 0); if (i > 0x100000) __trap(); }
        } else {
          for (int i = 0; ((ro >> (2 * (n - 28))) & 3) != 3; i++) { ro = __ballot_sync(~0u, ld_acq(fl + 32 + lane) != 0); if (i > 0x100000) __trap(); }
        }
        if (lane == 0) {
          const int s = n & 7;
          fence_async_all();
          mbar_wait(sb + B_FEMPTY + 8 * s, ((n >> 3) & 1) ^ 1);
          mbar_expect(sb + B_FFULL + 8 * s, 8192);
          bulk_ld(sb + s * FST, src + ch * 8192, 8192, sb + B_FFULL + 8 * s);
        }
        __syncwarp();
      }
      uint32_t last = 0;
      if (lane == 0) { __threadfence(); last = atomicAdd(&g_done, 1) == gridDim.x - 1; __threadfence(); }
      if (__shfl_sync(~0u, last, 0)) {
        for (int i = lane; i < (64 + 32 * 64) / 4; i += 32) reinterpret_cast<uint4*>(g_flags)[i] = make_uint4(0, 0, 0, 0);
        if (lane == 0) g_done = 0;
      }
    }
  } else if (wg == 2) {
    asm volatile("setmaxnreg.inc.sync.aligned.u32 %0;" ::"n"(REG_GEMM));
    float d0[64], d1[64];
    zero(d0); zero(d1);
    const uint32_t xl = dlo(sb + X_OFF, 16), wl = dlo(sb + W_OFF, 8192);
    constexpr uint32_t H128 = dhi(1024, 1);
    uint8_t* const hdst = a_tb + wq4 * 256 + lane * 4;
    const uint32_t grow = sb + G_OFF + (wq4 * 16 + (lane >> 2)) * 4;
#pragma unroll 1
    for (int st = 0; st < 3; st++) {
#pragma unroll 1
      for (int kc = 0; kc < 8; kc++) {
        const int s = kc & 3;
        if (st == 0) { mbar_wait(sb + B_XFULL + 8 * kc, 0); mbar_wait(sb + B_XFULL + 64 + 8 * kc, 0); }
        mbar_wait(sb + B_WFULL + 8 * s, (kc >> 2) & 1);
        const uint32_t a = xl + kc * 1024, b = wl + s * 1024;
#pragma unroll
        for (int k = 0; k < 4; k++) {
          wg_fence();
          mma_ss_t128(d0, mk64(a + 2 * k, H128), mk64(b + 128 * k, H128), (kc | k) != 0);
          mma_ss_t128(d1, mk64(a + 512 + 2 * k, H128), mk64(b + 128 * k, H128), (kc | k) != 0);
          wg_commit(); wg_wait<0>();
        }
        if (lane == 0) mbar_arrive2(sb + B_WEMPTY + 8 * s);
      }
      pin(d0); pin(d1);
      if (st == 0) mbar_wait(sb + B_GREADY, 0);
      const int hc = 7 * (cg >> 1) + 3 * half + st;
      store_h(d0, __uint_as_float(lds32(grow)), __uint_as_float(lds32(grow + 32)), hdst + hc * 8192);
      store_h(d1, __uint_as_float(lds32(grow + 256)), __uint_as_float(lds32(grow + 288)), hdst + A_BYTES + hc * 8192);
      bar_sync(3);
      if (tid == 256) { __threadfence(); st_rel(fl_tb + hc, 1); st_rel(fl_tb + 64 + hc, 1); }
      pin(d0); pin(d1);
    }
    {
#pragma unroll 1
      for (int kc = 0; kc < 8; kc++) {
        const int s = kc & 3;
        mbar_wait(sb + B_WFULL + 8 * s, (kc >> 2) & 1);
        const uint32_t a = xl + kc * 1024 + half * 512, b = wl + s * 1024;
#pragma unroll
        for (int k = 0; k < 4; k += 2) {
          wg_fence();
          mma_ss_t128(d0, mk64(a + 2 * k, H128), mk64(b + 128 * k, H128), (kc | k) != 0);
          mma_ss_t128(d0, mk64(a + 2 * k + 2, H128), mk64(b + 128 * k + 128, H128), 1);
          wg_commit(); wg_wait<0>();
        }
        if (lane == 0) mbar_arrive2(sb + B_WEMPTY + 8 * s);
      }
      pin(d0);
      if (lane == 0) mbar_arrive(sb + B_FFN1);
      const int hc = 7 * (cg >> 1) + 6;
      store_h(d0, __uint_as_float(lds32(grow + half * 256)), __uint_as_float(lds32(grow + half * 256 + 32)), hdst + half * A_BYTES + hc * 8192);
      bar_sync(3);
      if (tid == 256) { __threadfence(); st_rel(fl_tb + half * 64 + hc, 1); }
      pin(d0);
    }
    const uint32_t al = dlo(sb, 1024), bl = dlo(sb + 8192, 8192);
    constexpr uint32_t HA = dhi(128, 0);
#pragma unroll 1
    for (int n = 0; n < 36; n++) {
      const int s = n & 7;
      mbar_wait(sb + B_FFULL + 8 * s, (n >> 3) & 1);
      const uint32_t a = al + s * (FST >> 4), b = bl + s * (FST >> 4);
#pragma unroll
      for (int k = 0; k < 4; k += 2) {
        wg_fence();
        mma_ss_t128(d0, mk64(a + 128 * k, HA), mk64(b + 128 * k, H128), (n | k) != 0);
        mma_ss_t128(d0, mk64(a + 128 * k + 128, HA), mk64(b + 128 * k + 128, H128), 1);
        wg_commit(); wg_wait<0>();
      }
      if (lane == 0) mbar_arrive(sb + B_FEMPTY + 8 * s);
    }
    pin(d0);
    const uint32_t stg = sb + 4 * FST;
    const int r = wq4 * 16 + (lane & 7) + ((lane >> 3) & 1) * 8;
#pragma unroll
    for (int j = 0; j < 8; j++) {
      const int c16 = (2 * j + (lane >> 4)) & 7;
      const uint32_t ad = stg + (j >> 2) * 8192 + r * 128 + ((c16 ^ (r & 7)) << 4);
      asm volatile("stmatrix.sync.aligned.m8n8.x4.shared.b16 [%0], {%1,%2,%3,%4};" ::"r"(ad), "r"(pack2(d0[8 * j], d0[8 * j + 1])), "r"(pack2(d0[8 * j + 2], d0[8 * j + 3])),
                   "r"(pack2(d0[8 * j + 4], d0[8 * j + 5])), "r"(pack2(d0[8 * j + 6], d0[8 * j + 7])) : "memory");
    }
    asm volatile("fence.proxy.async.shared::cta;" ::: "memory");
    bar_sync(3);
    if (tid == 256) {
      const int col = (cg >> 1) * 128, row = tb * 128 + half * 64;
      asm volatile("cp.async.bulk.tensor.2d.global.shared::cta.bulk_group [%0, {%2, %3}], [%1];" ::"l"(&mp.out), "r"(stg), "r"(col), "r"(row) : "memory");
      asm volatile("cp.async.bulk.tensor.2d.global.shared::cta.bulk_group [%0, {%2, %3}], [%1];" ::"l"(&mp.out), "r"(stg + 8192), "r"(col + 64), "r"(row) : "memory");
      asm volatile("cp.async.bulk.commit_group;" ::: "memory");
      asm volatile("cp.async.bulk.wait_group.read 0;" ::: "memory");
    }
  } else {
    asm volatile("setmaxnreg.inc.sync.aligned.u32 %0;" ::"n"(REG_ATT));
    constexpr uint32_t H128 = dhi(1024, 1);
    const uint32_t xl = dlo(sb + X_OFF + wg * 8192, 16);
    if (cg < 4 && wg == half) {
      float d[8];
      zero(d);
      mbar_wait(sb + B_WKV, 0);
      const uint32_t wl = dlo(sb + KV_OFF, 16);
#pragma unroll 1
      for (int kc = 0; kc < 8; kc++) {
        mbar_wait(sb + B_XFULL + 64 * wg + 8 * kc, 0);
        wg_fence();
#pragma unroll
        for (int k = 0; k < 4; k++) mma_ss_t16(d, mk64(xl + kc * 1024 + 2 * k, H128), KD(wl + kc * 128 + 32 * k), 1);
        wg_commit();
      }
      wg_wait<0>(); pin(d);
      const uint32_t p0 = pack2(d[0], d[1]), p1 = pack2(d[2], d[3]), p2 = pack2(d[4], d[5]), p3 = pack2(d[6], d[7]);
      const int r = lane >> 2;
      uint8_t* dst = g_kv + (tb * 2 + wg) * 4096 + (cg >> 1) * 2048 + (wq4 * 16 + r) * 32 + (lane & 3) * 4;
      const int sw = (r >> 2) * 16;
      stg32(dst + sw, p0); stg32(dst + 256 + sw, p1); stg32(dst + (sw ^ 16), p2); stg32(dst + 256 + (sw ^ 16), p3);
      float n0 = sqsum2(p0) + sqsum2(p2), n1 = sqsum2(p1) + sqsum2(p3);
      n0 += __shfl_xor_sync(~0u, n0, 1); n1 += __shfl_xor_sync(~0u, n1, 1);
      n0 += __shfl_xor_sync(~0u, n0, 2); n1 += __shfl_xor_sync(~0u, n1, 2);
      const uint32_t mx = __reduce_max_sync(~0u, max(__float_as_uint(n0), __float_as_uint(n1)));
      if (lane == 0) sts32(sb + MISC_OFF + 48 + wq4 * 4, mx);
      bar_sync(1 + wg);
      if ((tid & 127) == 0) {
        const uint32_t m = max(max(lds32(sb + MISC_OFF + 48), lds32(sb + MISC_OFF + 52)), max(lds32(sb + MISC_OFF + 56), lds32(sb + MISC_OFF + 60)));
        __threadfence();
        st_rel(g_flags + (cg >> 1) * 32 + tb * 2 + wg, m | 1);
      }
    }
    uint32_t q[4][4];
    float g0, g1;
    {
      float d[32], e[4];
      zero(d); zero(e);
      const uint32_t wl = dlo(sb + W_OFF, 16), gl = dlo(sb + GW_OFF, 16);
#pragma unroll 1
      for (int s = 0; s < 4; s++) {
        mbar_wait(sb + B_XFULL + 64 * wg + 16 * s, 0);
        mbar_wait(sb + B_XFULL + 64 * wg + 16 * s + 8, 0);
        mbar_wait(sb + B_WQ + 8 * s, 0);
        wg_fence();
#pragma unroll
        for (int k = 0; k < 8; k++) mma_ss_t64(d, mk64(xl + (2 * s + (k >> 2)) * 1024 + 2 * (k & 3), H128), mk64(wl + s * 1024 + 128 * k, H128), 1);
        wg_commit(); wg_wait<0>();
        if (lane == 0) mbar_arrive(sb + B_WEMPTY + 8 * s);
      }
      pin(d);
      wg_fence();
#pragma unroll
      for (int k = 0; k < 32; k++) mma_ss_n8(e, mk64(xl + (k >> 2) * 1024 + 2 * (k & 3), H128), mk64(gl + 2 * k, dhi(128, 0)), 1);
      wg_commit();
      constexpr float QS = 0.25f * 1.4426950408889634f;
      float nm = 0.f;
#pragma unroll
      for (int h = 0; h < 4; h++) {
#pragma unroll
        for (int i = 0; i < 4; i++) q[h][i] = pack2(d[8 * h + 2 * i] * QS, d[8 * h + 2 * i + 1] * QS);
        float n0 = sqsum2(q[h][0]) + sqsum2(q[h][2]), n1 = sqsum2(q[h][1]) + sqsum2(q[h][3]);
        n0 += __shfl_xor_sync(~0u, n0, 1); n1 += __shfl_xor_sync(~0u, n1, 1);
        n0 += __shfl_xor_sync(~0u, n0, 2); n1 += __shfl_xor_sync(~0u, n1, 2);
        nm = __uint_as_float(max(__float_as_uint(nm), max(__float_as_uint(n0), __float_as_uint(n1))));
      }
      const uint32_t mx = __reduce_max_sync(~0u, __float_as_uint(nm));
      if (lane == 0) sts32(sb + MISC_OFF + warp * 4, mx);
      wg_wait<0>(); pin(e);
      const float z0 = __shfl_sync(~0u, e[0], lane & ~3), z1 = __shfl_sync(~0u, e[2], lane & ~3);
      g0 = 1.f / (1.f + __expf(-z0)); g1 = 1.f / (1.f + __expf(-z1));
      if ((lane & 3) == 0) {
        const uint32_t ga = sb + G_OFF + (wg * 64 + wq4 * 16 + (lane >> 2)) * 4;
        sts32(ga, __float_as_uint(0.5f * (1.f - g0))); sts32(ga + 32, __float_as_uint(0.5f * (1.f - g1)));
      }
      __syncwarp();
      if (lane == 0) mbar_arrive(sb + B_GREADY);
    }
    bar_sync(1 + wg);
    const uint32_t qa = sb + MISC_OFF + wg * 16;
    const float qm = __uint_as_float(max(max(lds32(qa), lds32(qa + 4)), max(lds32(qa + 8), lds32(qa + 12))));
    mbar_wait(sb + B_KVFULL, 0);
    const float km = __uint_as_float(lds32(sb + MISC_OFF + 32));
    const bool fast = !FORCE_SLOW && (qm * km <= 930.f);
    const uint32_t one = lds32(sb + ONES_OFF) & 0x3C003C00u;
    uint8_t* odst = a_tb + wg * A_BYTES + (224 + cg * 4) * 1024 + wq4 * 256 + lane * 4;
#pragma unroll 1
    for (int p = 0; p < 2; p++) {
      float o0[12], o1[12];
      if (fast) attn_fast(sb, q[0], q[1], o0, o1, lane, one);
      else attn_slow(sb, q[0], q[1], o0, o1, lane);
      store_o(o0, g0, g1, odst);
      store_o(o1, g0, g1, odst + 2048);
      bar_sync(1 + wg);
      if ((tid & 127) == 0) { __threadfence(); st_rel(fl_tb + wg * 64 + 32 + p * 8 + cg, 1); }
      odst += 32 * 1024;
#pragma unroll
      for (int i = 0; i < 4; i++) { q[0][i] = q[2][i]; q[1][i] = q[3][i]; }
    }
  }
}

typedef CUresult (*EncodeFn)(CUtensorMap*, CUtensorMapDataType, cuuint32_t, void*, const cuuint64_t*, const cuuint64_t*, const cuuint32_t*, const cuuint32_t*,
                             CUtensorMapInterleave, CUtensorMapSwizzle, CUtensorMapL2promotion, CUtensorMapFloatOOBfill);

void make_map(EncodeFn fn, CUtensorMap* m, const void* p, uint64_t cols, uint64_t rows, uint32_t bc, uint32_t br, CUtensorMapSwizzle sw) {
  cuuint64_t dims[2] = {cols, rows}, strides[1] = {cols * 2};
  cuuint32_t box[2] = {bc, br}, es[2] = {1, 1};
  fn(m, CU_TENSOR_MAP_DATA_TYPE_BFLOAT16, 2, const_cast<void*>(p), dims, strides, box, es, CU_TENSOR_MAP_INTERLEAVE_NONE, sw,
     CU_TENSOR_MAP_L2_PROMOTION_L2_128B, CU_TENSOR_MAP_FLOAT_OOB_FILL_NONE);
}

}

extern "C" void kernel_launch(void* const* d_in, const int* in_sizes, int n_in, void* d_out, int out_size) {
  void* fp = nullptr;
  cudaDriverEntryPointQueryResult qr;
  cudaGetDriverEntryPoint("cuTensorMapEncodeTiled", &fp, cudaEnableDefault, &qr);
  EncodeFn fn = (EncodeFn)fp;
  Maps mp;
  make_map(fn, &mp.x, d_in[0], D_, S_, 64, 64, CU_TENSOR_MAP_SWIZZLE_128B);
  make_map(fn, &mp.wq, d_in[1], D_, D_, 64, 64, CU_TENSOR_MAP_SWIZZLE_128B);
  make_map(fn, &mp.wk, d_in[2], 16, D_, 16, 256, CU_TENSOR_MAP_SWIZZLE_32B);
  make_map(fn, &mp.wv, d_in[3], 16, D_, 16, 256, CU_TENSOR_MAP_SWIZZLE_32B);
  make_map(fn, &mp.wo, d_in[4], D_, D_, 64, 32, CU_TENSOR_MAP_SWIZZLE_128B);
  make_map(fn, &mp.wg, d_in[6], F_, D_, 64, 64, CU_TENSOR_MAP_SWIZZLE_128B);
  make_map(fn, &mp.wu, d_in[7], F_, D_, 64, 64, CU_TENSOR_MAP_SWIZZLE_128B);
  make_map(fn, &mp.wd, d_in[8], D_, F_, 64, 64, CU_TENSOR_MAP_SWIZZLE_128B);
  make_map(fn, &mp.out, d_out, D_, S_, 64, 64, CU_TENSOR_MAP_SWIZZLE_128B);
  cudaFuncSetAttribute(fused_kernel, cudaFuncAttributeMaxDynamicSharedMemorySize, SMEM_BYTES);
  fused_kernel<<<128, 512, SMEM_BYTES, cudaStreamPerThread>>>(mp, (const __nv_bfloat16*)d_in[9], (const uint8_t*)d_in[8], (const uint8_t*)d_in[4]);
}
```

```cpp
#include <cuda_runtime.h>
#include <cuda_bf16.h>
#include <cuda.h>
#include <stdint.h>

#define POLYMASK 0x5555
#define REG_ATT 160
#define REG_GEMM 160
#define REG_PROD 32
#define FORCE_SLOW 0
#define NS_W 100
#define NS_KV 200
#define NS_F 50
#define NS_G 50
#define GW1 1
#define GW2 1

namespace {

constexpr int S_ = 2048, D_ = 512, F_ = 1792;

constexpr uint32_t sb = 1024;
constexpr uint32_t X_OFF = 0;
constexpr uint32_t W_OFF = 131072;
constexpr uint32_t KV_OFF = 196608;
constexpr uint32_t ONES_OFF = 229376;
constexpr uint32_t GW_OFF = 229888;
constexpr uint32_t G_OFF = 231040;
constexpr uint32_t MISC_OFF = 231552;
constexpr uint32_t BAR_OFF = 231616;
constexpr uint32_t B_XFULL = BAR_OFF;
constexpr uint32_t B_PUB = B_XFULL + 64;
constexpr uint32_t B_WKV = B_XFULL + 128;
constexpr uint32_t B_GREADY = B_WKV + 8;
constexpr uint32_t B_FFN1 = B_GREADY + 8;
constexpr uint32_t B_WFULL = B_FFN1 + 8;
constexpr uint32_t B_WEMPTY = B_WFULL + 32;
constexpr uint32_t B_KVFULL = B_WEMPTY + 32;
constexpr uint32_t B_KVEMPTY = B_KVFULL + 32;
constexpr uint32_t B_FFULL = B_KVEMPTY + 32;
constexpr uint32_t B_FEMPTY = B_FFULL + 64;
constexpr uint32_t B_WQ = B_FEMPTY + 64;
constexpr uint32_t SMEM_BYTES = B_WQ + 32;
constexpr uint32_t FST = 24576;
static_assert(SMEM_BYTES <= 232448, "smem");

constexpr int A_BYTES = 288 * 1024;
__device__ __align__(1024) uint8_t g_kv[32 * 4096];
__device__ __align__(1024) uint8_t g_a[32 * A_BYTES];
__device__ __align__(256) uint32_t g_flags[64 + 32 * 64];
__device__ uint32_t g_done;

#define EV(i)
struct Maps { CUtensorMap x, wq, wk, wv, wo, wg, wu, wd, out; };

__device__ __forceinline__ void wg_fence() { asm volatile("wgmma.fence.sync.aligned;" ::: "memory"); }
__device__ __forceinline__ void wg_commit() { asm volatile("wgmma.commit_group.sync.aligned;" ::: "memory"); }
template <int N> __device__ __forceinline__ void wg_wait() { asm volatile("wgmma.wait_group.sync.aligned %0;" ::"n"(N) : "memory"); }
template <int N> __device__ __forceinline__ void pin(float (&d)[N]) {
#pragma unroll
  for (int i = 0; i < N; i++) asm volatile("" : "+f"(d[i])::"memory");
}
template <int N> __device__ __forceinline__ void pinu(uint32_t (&d)[N]) {
#pragma unroll
  for (int i = 0; i < N; i++) asm volatile("" : "+r"(d[i])::"memory");
}
template <int N> __device__ __forceinline__ void zero(float (&d)[N]) {
#pragma unroll
  for (int i = 0; i < N; i++) d[i] = 0.f;
  pin(d);
}
__device__ __forceinline__ uint64_t mk64(uint32_t lo, uint32_t hi) { return ((uint64_t)hi << 32) | lo; }
__host__ __device__ constexpr uint32_t dhi(uint32_t sbo, uint32_t sw) { return (sbo >> 4) | (sw << 30); }
__device__ __forceinline__ uint32_t dlo(uint32_t addr, uint32_t lbo) { return (addr >> 4) | ((lbo >> 4) << 16); }

__device__ __forceinline__ void mbar_init(uint32_t b, uint32_t n) { asm volatile("mbarrier.init.shared::cta.b64 [%0], %1;" ::"r"(b), "r"(n) : "memory"); }
__device__ __forceinline__ void mbar_arrive(uint32_t b) { asm volatile("mbarrier.arrive.shared::cta.b64 _, [%0];" ::"r"(b) : "memory"); }
__device__ __forceinline__ void mbar_arrive2(uint32_t b) { asm volatile("mbarrier.arrive.shared::cta.b64 _, [%0], 2;" ::"r"(b) : "memory"); }
__device__ __forceinline__ void mbar_expect(uint32_t b, uint32_t bytes) { asm volatile("mbarrier.arrive.expect_tx.shared::cta.b64 _, [%0], %1;" ::"r"(b), "r"(bytes) : "memory"); }
__device__ __forceinline__ void mbar_wait(uint32_t b, uint32_t parity) {
  asm volatile(
      "{\n.reg .pred p;\n.reg .u32 c;\n"
      "mbarrier.try_wait.parity.shared::cta.b64 p, [%0], %1;\n"
      "@p bra DONE;\n"
      "mov.u32 c, 0;\n"
      "SPIN:\n"
      "mbarrier.try_wait.parity.shared::cta.b64 p, [%0], %1;\n"
      "@p bra DONE;\n"
      "add.u32 c, c, 1;\n"
      "setp.lt.u32 p, c, 0x100000;\n"
      "@p bra SPIN;\n"
      "trap;\n"
      "DONE:\n}\n" ::"r"(b), "r"(parity) : "memory");
}
template <int NS> __device__ __forceinline__ void mbar_wait_sleep(uint32_t b, uint32_t parity) {
  asm volatile(
      "{\n.reg .pred p;\n.reg .u32 c;\n"
      "mov.u32 c, 0;\n"
      "SPIN:\n"
      "mbarrier.test_wait.parity.shared::cta.b64 p, [%0], %1;\n"
      "@p bra.uni DONE;\n"
      "nanosleep.u32 %2;\n"
      "add.u32 c, c, 1;\n"
      "setp.lt.u32 p, c, 0x100000;\n"
      "@p bra.uni SPIN;\n"
      "trap;\n"
      "DONE:\n}\n" ::"r"(b), "r"(parity), "n"(NS) : "memory");
}
#define ELECT "{\n.reg .pred p;\nelect.sync _|p, 0xffffffff;\n@p mbarrier.arrive.expect_tx.shared::cta.b64 _, [%0], %1;\n"
__device__ __forceinline__ void u_tma3d(uint32_t bar, uint32_t bytes, uint32_t dst, const CUtensorMap* m, int c0, int c1, int c2) {
  asm volatile(ELECT "@p cp.async.bulk.tensor.3d.shared::cluster.global.mbarrier::complete_tx::bytes [%2], [%3, {%4, %5, %6}], [%0];\n}\n" ::"r"(bar), "r"(bytes), "r"(dst), "l"(m), "r"(c0), "r"(c1), "r"(c2) : "memory");
}
__device__ __forceinline__ void u_tma2d_pair(uint32_t bar, uint32_t dst, const CUtensorMap* m0, const CUtensorMap* m1, int c0, int c1, int c1b) {
  asm volatile(ELECT "@p cp.async.bulk.tensor.2d.shared::cluster.global.mbarrier::complete_tx::bytes [%2], [%3, {%5, %6}], [%0];\n"
               "@p cp.async.bulk.tensor.2d.shared::cluster.global.mbarrier::complete_tx::bytes [%2 + 8192], [%4, {%5, %7}], [%0];\n}\n" ::"r"(bar), "r"(16384), "r"(dst), "l"(m0), "l"(m1), "r"(c0), "r"(c1), "r"(c1b) : "memory");
}
__device__ __forceinline__ void u_bulk(uint32_t bar, uint32_t bytes, uint32_t dst, const void* src) {
  asm volatile(ELECT "@p cp.async.bulk.shared::cluster.global.mbarrier::complete_tx::bytes [%2], [%3], %1, [%0];\n}\n" ::"r"(bar), "r"(bytes), "r"(dst), "l"(src) : "memory");
}
__device__ __forceinline__ void u_prefetch(const void* src, uint32_t bytes) {
  asm volatile("{\n.reg .pred p;\nelect.sync _|p, 0xffffffff;\n@p cp.async.bulk.prefetch.L2.global [%0], %1;\n}\n" ::"l"(src), "r"(bytes) : "memory");
}
__device__ __forceinline__ void fence_gpu() { asm volatile("fence.acq_rel.gpu;" ::: "memory"); }
__device__ __forceinline__ void st_rlx(uint32_t* p, uint32_t v) { asm volatile("st.relaxed.gpu.global.u32 [%0], %1;" ::"l"(p), "r"(v) : "memory"); }
__device__ __forceinline__ uint64_t ld_acq64(const uint32_t* p) { uint64_t v; asm volatile("ld.acquire.gpu.global.u64 %0, [%1];" : "=l"(v) : "l"(p) : "memory"); return v; }
__device__ __forceinline__ void tma2d(uint32_t dst, const CUtensorMap* m, int c0, int c1, uint32_t bar) {
  asm volatile("cp.async.bulk.tensor.2d.shared::cluster.global.mbarrier::complete_tx::bytes [%0], [%1, {%3, %4}], [%2];" ::"r"(dst), "l"(m), "r"(bar), "r"(c0), "r"(c1) : "memory");
}
__device__ __forceinline__ void bulk_ld(uint32_t dst, const void* src, uint32_t bytes, uint32_t bar) {
  asm volatile("cp.async.bulk.shared::cluster.global.mbarrier::complete_tx::bytes [%0], [%1], %2, [%3];" ::"r"(dst), "l"(src), "r"(bytes), "r"(bar) : "memory");
}
__device__ __forceinline__ void l2_prefetch(const void* src, uint32_t bytes) {
  asm volatile("cp.async.bulk.prefetch.L2.global [%0], %1;" ::"l"(src), "r"(bytes) : "memory");
}
__device__ __forceinline__ uint32_t ld_acq(const uint32_t* p) { uint32_t v; asm volatile("ld.acquire.gpu.global.u32 %0, [%1];" : "=r"(v) : "l"(p) : "memory"); return v; }
__device__ __forceinline__ void st_rel(uint32_t* p, uint32_t v) { asm volatile("st.release.gpu.global.u32 [%0], %1;" ::"l"(p), "r"(v) : "memory"); }
__device__ __forceinline__ void fence_async_all() { asm volatile("fence.proxy.async;" ::: "memory"); }
__device__ __forceinline__ void fence_async_gl() { asm volatile("fence.proxy.async.global;" ::: "memory"); }
__device__ __forceinline__ void bar_sync(int id) { asm volatile("bar.sync %0, 128;" ::"r"(id) : "memory"); }
__device__ __forceinline__ uint32_t pack2(float lo, float hi) { uint32_t r; asm("cvt.rn.bf16x2.f32 %0, %1, %2;" : "=r"(r) : "f"(hi), "f"(lo)); return r; }
__device__ __forceinline__ float ex2(float a) { float r; asm("ex2.approx.ftz.f32 %0, %1;" : "=f"(r) : "f"(a)); return r; }
__device__ __forceinline__ float sqsum2(uint32_t p) { float a = __uint_as_float(p << 16), b = __uint_as_float(p & 0xffff0000u); return fmaf(a, a, b * b); }
__device__ __forceinline__ void stg32(void* p, uint32_t v) { asm volatile("st.global.u32 [%0], %1;" ::"l"(p), "r"(v) : "memory"); }
__device__ __forceinline__ void sts32(uint32_t a, uint32_t v) { asm volatile("st.shared.u32 [%0], %1;" ::"r"(a), "r"(v) : "memory"); }
__device__ __forceinline__ uint32_t lds32(uint32_t a) { uint32_t v; asm volatile("ld.shared.u32 %0, [%1];" : "=r"(v) : "r"(a) : "memory"); return v; }

__device__ __forceinline__ void mma_qk(float (&d)[32], const uint32_t (&a)[4], uint64_t b) {
  asm volatile("{\n.reg .pred p;\nsetp.ne.b32 p, 0, 0;\n"
    "wgmma.mma_async.sync.aligned.m64n64k16.f32.bf16.bf16 {%0,%1,%2,%3,%4,%5,%6,%7,%8,%9,%10,%11,%12,%13,%14,%15,%16,%17,%18,%19,%20,%21,%22,%23,%24,%25,%26,%27,%28,%29,%30,%31}, {%32,%33,%34,%35}, %36, p, 1, 1, 0;\n}\n"
    : "+f"(d[0]),"+f"(d[1]),"+f"(d[2]),"+f"(d[3]),"+f"(d[4]),"+f"(d[5]),"+f"(d[6]),"+f"(d[7]),"+f"(d[8]),"+f"(d[9]),"+f"(d[10]),"+f"(d[11]),"+f"(d[12]),"+f"(d[13]),"+f"(d[14]),"+f"(d[15]),"+f"(d[16]),"+f"(d[17]),"+f"(d[18]),"+f"(d[19]),"+f"(d[20]),"+f"(d[21]),"+f"(d[22]),"+f"(d[23]),"+f"(d[24]),"+f"(d[25]),"+f"(d[26]),"+f"(d[27]),"+f"(d[28]),"+f"(d[29]),"+f"(d[30]),"+f"(d[31]) : "r"(a[0]),"r"(a[1]),"r"(a[2]),"r"(a[3]),"l"(b));
}
__device__ __forceinline__ void mma_pv(float (&d)[12], const uint32_t (&a)[4], uint64_t b) {
  asm volatile("{\n.reg .pred p;\nsetp.ne.b32 p, 1, 0;\n"
    "wgmma.mma_async.sync.aligned.m64n24k16.f32.bf16.bf16 {%0,%1,%2,%3,%4,%5,%6,%7,%8,%9,%10,%11}, {%12,%13,%14,%15}, %16, p, 1, 1, 1;\n}\n"
    : "+f"(d[0]),"+f"(d[1]),"+f"(d[2]),"+f"(d[3]),"+f"(d[4]),"+f"(d[5]),"+f"(d[6]),"+f"(d[7]),"+f"(d[8]),"+f"(d[9]),"+f"(d[10]),"+f"(d[11]) : "r"(a[0]),"r"(a[1]),"r"(a[2]),"r"(a[3]),"l"(b));
}
__device__ __forceinline__ void mma_ss_t128(float (&d)[64], uint64_t a, uint64_t b, int acc) {
  asm volatile("{\n.reg .pred p;\nsetp.ne.b32 p, %66, 0;\n"
    "wgmma.mma_async.sync.aligned.m64n128k16.f32.bf16.bf16 {%0,%1,%2,%3,%4,%5,%6,%7,%8,%9,%10,%11,%12,%13,%14,%15,%16,%17,%18,%19,%20,%21,%22,%23,%24,%25,%26,%27,%28,%29,%30,%31,%32,%33,%34,%35,%36,%37,%38,%39,%40,%41,%42,%43,%44,%45,%46,%47,%48,%49,%50,%51,%52,%53,%54,%55,%56,%57,%58,%59,%60,%61,%62,%63}, %64, %65, p, 1, 1, 0, 1;\n}\n"
    : "+f"(d[0]),"+f"(d[1]),"+f"(d[2]),"+f"(d[3]),"+f"(d[4]),"+f"(d[5]),"+f"(d[6]),"+f"(d[7]),"+f"(d[8]),"+f"(d[9]),"+f"(d[10]),"+f"(d[11]),"+f"(d[12]),"+f"(d[13]),"+f"(d[14]),"+f"(d[15]),"+f"(d[16]),"+f"(d[17]),"+f"(d[18]),"+f"(d[19]),"+f"(d[20]),"+f"(d[21]),"+f"(d[22]),"+f"(d[23]),"+f"(d[24]),"+f"(d[25]),"+f"(d[26]),"+f"(d[27]),"+f"(d[28]),"+f"(d[29]),"+f"(d[30]),"+f"(d[31]),"+f"(d[32]),"+f"(d[33]),"+f"(d[34]),"+f"(d[35]),"+f"(d[36]),"+f"(d[37]),"+f"(d[38]),"+f"(d[39]),"+f"(d[40]),"+f"(d[41]),"+f"(d[42]),"+f"(d[43]),"+f"(d[44]),"+f"(d[45]),"+f"(d[46]),"+f"(d[47]),"+f"(d[48]),"+f"(d[49]),"+f"(d[50]),"+f"(d[51]),"+f"(d[52]),"+f"(d[53]),"+f"(d[54]),"+f"(d[55]),"+f"(d[56]),"+f"(d[57]),"+f"(d[58]),"+f"(d[59]),"+f"(d[60]),"+f"(d[61]),"+f"(d[62]),"+f"(d[63]) : "l"(a),"l"(b),"r"(acc));
}
__device__ __forceinline__ void mma_ss_t64(float (&d)[32], uint64_t a, uint64_t b, int acc) {
  asm volatile("{\n.reg .pred p;\nsetp.ne.b32 p, %34, 0;\n"
    "wgmma.mma_async.sync.aligned.m64n64k16.f32.bf16.bf16 {%0,%1,%2,%3,%4,%5,%6,%7,%8,%9,%10,%11,%12,%13,%14,%15,%16,%17,%18,%19,%20,%21,%22,%23,%24,%25,%26,%27,%28,%29,%30,%31}, %32, %33, p, 1, 1, 0, 1;\n}\n"
    : "+f"(d[0]),"+f"(d[1]),"+f"(d[2]),"+f"(d[3]),"+f"(d[4]),"+f"(d[5]),"+f"(d[6]),"+f"(d[7]),"+f"(d[8]),"+f"(d[9]),"+f"(d[10]),"+f"(d[11]),"+f"(d[12]),"+f"(d[13]),"+f"(d[14]),"+f"(d[15]),"+f"(d[16]),"+f"(d[17]),"+f"(d[18]),"+f"(d[19]),"+f"(d[20]),"+f"(d[21]),"+f"(d[22]),"+f"(d[23]),"+f"(d[24]),"+f"(d[25]),"+f"(d[26]),"+f"(d[27]),"+f"(d[28]),"+f"(d[29]),"+f"(d[30]),"+f"(d[31]) : "l"(a),"l"(b),"r"(acc));
}
__device__ __forceinline__ void mma_ss_t16(float (&d)[8], uint64_t a, uint64_t b, int acc) {
  asm volatile("{\n.reg .pred p;\nsetp.ne.b32 p, %10, 0;\n"
    "wgmma.mma_async.sync.aligned.m64n16k16.f32.bf16.bf16 {%0,%1,%2,%3,%4,%5,%6,%7}, %8, %9, p, 1, 1, 0, 1;\n}\n"
    : "+f"(d[0]),"+f"(d[1]),"+f"(d[2]),"+f"(d[3]),"+f"(d[4]),"+f"(d[5]),"+f"(d[6]),"+f"(d[7]) : "l"(a),"l"(b),"r"(acc));
}
__device__ __forceinline__ void mma_ss_n8(float (&d)[4], uint64_t a, uint64_t b, int acc) {
  asm volatile("{\n.reg .pred p;\nsetp.ne.b32 p, %6, 0;\n"
    "wgmma.mma_async.sync.aligned.m64n8k16.f32.bf16.bf16 {%0,%1,%2,%3}, %4, %5, p, 1, 1, 0, 0;\n}\n"
    : "+f"(d[0]),"+f"(d[1]),"+f"(d[2]),"+f"(d[3]) : "l"(a),"l"(b),"r"(acc));
}

__device__ __forceinline__ uint32_t exp2_pair_fma(float a, float b, uint32_t one) {
  float da = a + 8224.f, db = b + 8224.f;
  uint32_t u = __byte_perm(__float_as_uint(da), __float_as_uint(db), 0x5410);
  uint32_t g, t;
  asm("lop3.b32 %0, %1, 0x03FF03FF, %2, 0xEA;" : "=r"(g) : "r"(u), "r"(one));
  uint32_t un = u & 0xFC00FC00u;
  asm("fma.rn.f16x2 %0, %1, %2, %3;" : "=r"(t) : "r"(g), "r"(0x10F910F9u), "r"(0x836B836Bu));
  asm("fma.rn.f16x2 %0, %1, %2, %3;" : "=r"(t) : "r"(t), "r"(g), "r"(0x1B9D1B9Du));
  asm("fma.rn.f16x2 %0, %1, %2, %3;" : "=r"(t) : "r"(t), "r"(g), "r"(0x2F3A2F3Au));
  return t + (un >> 3);
}
template <int J> __device__ __forceinline__ void sm_unit(const float (&s)[32], uint32_t (&p)[4], uint32_t one) {
#pragma unroll
  for (int i = 0; i < 4; i++) {
    const int j = J * 4 + i;
    if ((POLYMASK >> j) & 1) p[i] = exp2_pair_fma(s[2 * j], s[2 * j + 1], one);
    else p[i] = pack2(ex2(s[2 * j]), ex2(s[2 * j + 1]));
  }
}

#define KD(lo) mk64((lo), dhi(256, 3))
#define VO(x) ((uint32_t)(x) - ((uint32_t)(x) << 16))

__device__ __forceinline__ void attn_fast(const uint32_t (&q0)[4], const uint32_t (&q1)[4], float (&o0)[12], float (&o1)[12], int lane, uint32_t one) {
  const uint32_t kvfull = sb + B_KVFULL, kvempty = sb + B_KVEMPTY;
  const uint32_t kbase = dlo(sb + KV_OFF, 16), vbase = dlo(sb + KV_OFF, ONES_OFF - KV_OFF);
  float s0[32], s1[32];
  zero(s0); zero(s1); zero(o0); zero(o1);
  {
    uint32_t p0[4]={0,0,0,0}; pinu(p0);
    uint32_t p1[4]={0,0,0,0}; pinu(p1);
    uint32_t p2[4]={0,0,0,0}; pinu(p2);
    uint32_t p3[4]={0,0,0,0}; pinu(p3);
    wg_fence(); mma_qk(s0, q0, KD(kbase)); wg_commit(); wg_wait<0>(); pin(s0);
    uint32_t vprev = vbase - VO(512);
#pragma unroll 1
    for (int it = 0; it < 8; it++) {
      const uint32_t sA = (it & 1) * 2, ph = (it >> 1) & 1, phn = ((it + 1) >> 1) & 1;
      const uint32_t kcur = kbase + sA * 512, knxt = kbase + (sA ^ 2) * 512, vcur = vbase + VO(sA * 512);
      wg_fence();
      mma_qk(s1,q1,KD(kcur+0));
      mma_pv(o1,p2,KD(vprev+VO(960)));
      mma_pv(o1,p3,KD(vprev+VO(992)));
      wg_commit();
      sm_unit<0>(s0,p0,one);
      sm_unit<1>(s0,p1,one);
      wg_fence();
      mma_pv(o0,p0,KD(vcur+VO(128)));
      mma_pv(o0,p1,KD(vcur+VO(160)));
      wg_commit();
      wg_wait<1>();
      if (lane==0 && it!=0) mbar_arrive(kvempty+8*((sA^2)+1));
      sm_unit<2>(s0,p2,one);
      sm_unit<3>(s0,p3,one);
      wg_fence();
      mma_qk(s0,q0,KD(kcur+256));
      mma_pv(o0,p2,KD(vcur+VO(192)));
      mma_pv(o0,p3,KD(vcur+VO(224)));
      wg_commit();
      wg_wait<1>(); pin(s1);
      sm_unit<0>(s1,p0,one);
      sm_unit<1>(s1,p1,one);
      wg_fence();
      mma_pv(o1,p0,KD(vcur+VO(128)));
      mma_pv(o1,p1,KD(vcur+VO(160)));
      wg_commit();
      wg_wait<1>();
      sm_unit<2>(s1,p2,one);
      sm_unit<3>(s1,p3,one);
      wg_fence();
      mma_qk(s1,q1,KD(kcur+256));
      mma_pv(o1,p2,KD(vcur+VO(192)));
      mma_pv(o1,p3,KD(vcur+VO(224)));
      wg_commit();
      wg_wait<1>(); pin(s0);
      sm_unit<0>(s0,p0,one);
      sm_unit<1>(s0,p1,one);
      wg_fence();
      mma_pv(o0,p0,KD(vcur+VO(384)));
      mma_pv(o0,p1,KD(vcur+VO(416)));
      wg_commit();
      wg_wait<1>();
      sm_unit<2>(s0,p2,one);
      sm_unit<3>(s0,p3,one);
      mbar_wait(kvfull+8*(sA+1), ph);
      wg_fence();
      mma_qk(s0,q0,KD(kcur+512));
      mma_pv(o0,p2,KD(vcur+VO(448)));
      mma_pv(o0,p3,KD(vcur+VO(480)));
      wg_commit();
      wg_wait<1>(); pin(s1);
      sm_unit<0>(s1,p0,one);
      sm_unit<1>(s1,p1,one);
      wg_fence();
      mma_pv(o1,p0,KD(vcur+VO(384)));
      mma_pv(o1,p1,KD(vcur+VO(416)));
      wg_commit();
      wg_wait<1>();
      sm_unit<2>(s1,p2,one);
      sm_unit<3>(s1,p3,one);
      wg_fence();
      mma_qk(s1,q1,KD(kcur+512));
      mma_pv(o1,p2,KD(vcur+VO(448)));
      mma_pv(o1,p3,KD(vcur+VO(480)));
      wg_commit();
      wg_wait<1>(); pin(s0);
      sm_unit<0>(s0,p0,one);
      sm_unit<1>(s0,p1,one);
      wg_fence();
      mma_pv(o0,p0,KD(vcur+VO(640)));
      mma_pv(o0,p1,KD(vcur+VO(672)));
      wg_commit();
      wg_wait<1>();
      if (lane==0) mbar_arrive(kvempty+8*sA);
      sm_unit<2>(s0,p2,one);
      sm_unit<3>(s0,p3,one);
      wg_fence();
      mma_qk(s0,q0,KD(kcur+768));
      mma_pv(o0,p2,KD(vcur+VO(704)));
      mma_pv(o0,p3,KD(vcur+VO(736)));
      wg_commit();
      wg_wait<1>(); pin(s1);
      sm_unit<0>(s1,p0,one);
      sm_unit<1>(s1,p1,one);
      wg_fence();
      mma_pv(o1,p0,KD(vcur+VO(640)));
      mma_pv(o1,p1,KD(vcur+VO(672)));
      wg_commit();
      wg_wait<1>();
      sm_unit<2>(s1,p2,one);
      sm_unit<3>(s1,p3,one);
      wg_fence();
      mma_qk(s1,q1,KD(kcur+768));
      mma_pv(o1,p2,KD(vcur+VO(704)));
      mma_pv(o1,p3,KD(vcur+VO(736)));
      wg_commit();
      wg_wait<1>(); pin(s0);
      sm_unit<0>(s0,p0,one);
      sm_unit<1>(s0,p1,one);
      wg_fence();
      mma_pv(o0,p0,KD(vcur+VO(896)));
      mma_pv(o0,p1,KD(vcur+VO(928)));
      wg_commit();
      wg_wait<1>();
      sm_unit<2>(s0,p2,one);
      sm_unit<3>(s0,p3,one);
      mbar_wait(kvfull+8*(sA^2), phn);
      wg_fence();
      mma_qk(s0,q0,KD(knxt));
      mma_pv(o0,p2,KD(vcur+VO(960)));
      mma_pv(o0,p3,KD(vcur+VO(992)));
      wg_commit();
      wg_wait<1>(); pin(s1);
      sm_unit<0>(s1,p0,one);
      sm_unit<1>(s1,p1,one);
      wg_fence();
      mma_pv(o1,p0,KD(vcur+VO(896)));
      mma_pv(o1,p1,KD(vcur+VO(928)));
      wg_commit();
      wg_wait<1>();
      sm_unit<2>(s1,p2,one);
      sm_unit<3>(s1,p3,one);
      wg_wait<0>(); pin(s0); pin(o0); pin(o1);
      vprev = vcur;
    }
    wg_fence();
    mma_pv(o1,p2,KD(vprev+VO(960)));
    mma_pv(o1,p3,KD(vprev+VO(992)));
    wg_commit(); wg_wait<0>(); pin(o0); pin(o1);
    if (lane == 0) mbar_arrive(kvempty + 8 * 3);
  }
}

__device__ __forceinline__ void slow_tile(const uint32_t (&q)[4], float (&o)[12], float& m0, float& m1, uint32_t kd, uint32_t vd) {
  float s[32];
  wg_fence(); mma_qk(s, q, KD(kd)); wg_commit(); wg_wait<0>(); pin(s);
  float a = m0, b = m1;
#pragma unroll
  for (int j = 0; j < 8; j++) { a = fmaxf(a, fmaxf(s[4 * j], s[4 * j + 1])); b = fmaxf(b, fmaxf(s[4 * j + 2], s[4 * j + 3])); }
  a = fmaxf(a, __shfl_xor_sync(~0u, a, 1)); a = fmaxf(a, __shfl_xor_sync(~0u, a, 2));
  b = fmaxf(b, __shfl_xor_sync(~0u, b, 1)); b = fmaxf(b, __shfl_xor_sync(~0u, b, 2));
  const float ca = ex2(m0 - a), cb = ex2(m1 - b);
  m0 = a; m1 = b;
#pragma unroll
  for (int j = 0; j < 3; j++) { o[4 * j] *= ca; o[4 * j + 1] *= ca; o[4 * j + 2] *= cb; o[4 * j + 3] *= cb; }
  uint32_t p[4][4];
#pragma unroll
  for (int j = 0; j < 8; j++) {
    p[j >> 1][(j & 1) * 2] = pack2(ex2(s[4 * j] - a), ex2(s[4 * j + 1] - a));
    p[j >> 1][(j & 1) * 2 + 1] = pack2(ex2(s[4 * j + 2] - b), ex2(s[4 * j + 3] - b));
  }
  pin(o);
  wg_fence();
#pragma unroll
  for (int j = 0; j < 4; j++) mma_pv(o, p[j], KD(vd + VO(128 + 32 * j)));
  wg_commit(); wg_wait<0>(); pin(o);
}
__device__ __forceinline__ void attn_slow(const uint32_t (&q0)[4], const uint32_t (&q1)[4], float (&o0)[12], float (&o1)[12], int lane) {
  const uint32_t kbase = dlo(sb + KV_OFF, 16), vbase = dlo(sb + KV_OFF, ONES_OFF - KV_OFF);
  zero(o0); zero(o1);
  float m00 = -INFINITY, m01 = -INFINITY, m10 = -INFINITY, m11 = -INFINITY;
#pragma unroll 1
  for (int c = 0; c < 32; c++) {
    const uint32_t off = (c & 7) * 256;
    slow_tile(q0, o0, m00, m01, kbase + off, vbase + VO(off));
    slow_tile(q1, o1, m10, m11, kbase + off, vbase + VO(off));
    if (c & 1) {
      if (lane == 0) mbar_arrive(sb + B_KVEMPTY + 8 * ((c >> 1) & 3));
      const int n = (c >> 1) + 1;
      mbar_wait(sb + B_KVFULL + 8 * (n & 3), (n >> 2) & 1);
    }
  }
}

__device__ __forceinline__ void store_o(const float (&o)[12], float g0, float g1, uint8_t* dst) {
  const float a = __fdividef(g0, o[8]), b = __fdividef(g1, o[10]);
  stg32(dst, pack2(o[0] * a, o[1] * a));
  stg32(dst + 128, pack2(o[2] * b, o[3] * b));
  stg32(dst + 1024, pack2(o[4] * a, o[5] * a));
  stg32(dst + 1152, pack2(o[6] * b, o[7] * b));
}

template <bool FAST> __device__ __forceinline__ void attn_passes(uint32_t (&q)[4][4], float g0, float g1, uint8_t* odst, uint32_t* oflag, int wg, uint32_t one) {
  const int lane = threadIdx.x & 31;
#pragma unroll 1
  for (int p = 0; p < 2; p++) {
    float o0[12], o1[12];
    if (FAST) attn_fast(q[0], q[1], o0, o1, lane, one);
    else attn_slow(q[0], q[1], o0, o1, lane);
    store_o(o0, g0, g1, odst);
    store_o(o1, g0, g1, odst + 2048);
    if (p == 0) {
      __syncwarp();
      if (lane == 0) mbar_arrive(sb + B_PUB + 32);
    } else {
      bar_sync(1 + wg);
      if ((threadIdx.x & 127) == 0) { fence_gpu(); st_rlx(oflag, 1); }
    }
    odst += 32 * 1024;
#pragma unroll
    for (int i = 0; i < 4; i++) { q[0][i] = q[2][i]; q[1][i] = q[3][i]; }
  }
}

__device__ __forceinline__ float geglu(float x, float u, float c) {
  const float y = x * fmaf(x * x, 0.044715f * 0.7978845608028654f, 0.7978845608028654f);
  float t; asm("tanh.approx.f32 %0, %1;" : "=f"(t) : "f"(y));
  const float h = x * u * c;
  return fmaf(h, t, h);
}
__device__ __forceinline__ void store_h(const float (&d)[64], float c0, float c1, uint8_t* dst) {
#pragma unroll
  for (int j = 0; j < 8; j++) {
    stg32(dst + j * 1024, pack2(geglu(d[4 * j], d[32 + 4 * j], c0), geglu(d[4 * j + 1], d[33 + 4 * j], c0)));
    stg32(dst + j * 1024 + 128, pack2(geglu(d[4 * j + 2], d[34 + 4 * j], c1), geglu(d[4 * j + 3], d[35 + 4 * j], c1)));
  }
}

__global__ void __launch_bounds__(512, 1)
fused_kernel(const __grid_constant__ Maps mp, const __nv_bfloat16* __restrict__ gate_w, const uint8_t* __restrict__ wd_raw, const uint8_t* __restrict__ wo_raw) {
  extern __shared__ __align__(1024) uint8_t smem[];
  const int tid = threadIdx.x, lane = tid & 31;
  const int warp = __shfl_sync(~0u, tid >> 5, 0);
  const int wg = warp >> 2, wq4 = warp & 3;
  const int tb = blockIdx.x >> 3, cg = blockIdx.x & 7;
  const int half = cg & 1;

  if (warp == 12) {
    if (lane == 0) {
      EV(0);
      if ((uint32_t)__cvta_generic_to_shared(smem) != sb) __trap();
      for (int i = 0; i < 8; i++) mbar_init(sb + B_XFULL + 8 * i, 1);
      mbar_init(sb + B_WKV, 1);
      for (int i = 0; i < 4; i++) mbar_init(sb + B_WQ + 8 * i, i == 3 ? 2 : 1);
      asm volatile("fence.mbarrier_init.release.cluster;" ::: "memory");
    }
    __syncwarp();
    if (cg < 4) { const CUtensorMap* m = cg < 2 ? &mp.wk : &mp.wv; u_tma2d_pair(sb + B_WKV, sb + KV_OFF, m, m, 0, 0, 256); }
#pragma unroll
    for (int hh = 0; hh < 2; hh++) {
      const int h = hh ^ half;
#pragma unroll
      for (int j = 0; j < 4; j++) u_tma3d(sb + B_XFULL + 32 * h + 8 * j, 16384, sb + X_OFF + h * 65536 + j * 16384, &mp.x, 0, tb * 128 + h * 64, 2 * j);
#pragma unroll
      for (int s = 2 * hh; s < 2 * hh + 2; s++) u_tma3d(sb + B_WQ + 8 * s, 16384, sb + W_OFF + s * 16384, &mp.wq, cg * 32, s * 128, 0);
    }
    u_bulk(sb + B_WQ + 24, 1024, sb + GW_OFF, gate_w);
  } else if (tid == 416) {
    mbar_init(sb + B_GREADY, 8); mbar_init(sb + B_FFN1, 4);
    for (int i = 0; i < 4; i++) { mbar_init(sb + B_WFULL + 8 * i, 1); mbar_init(sb + B_WEMPTY + 8 * i, 8); mbar_init(sb + B_KVFULL + 8 * i, 1); mbar_init(sb + B_KVEMPTY + 8 * i, 8); mbar_init(sb + B_PUB + 8 * i, 4); }
    mbar_init(sb + B_PUB + 32, 8);
    for (int i = 0; i < 8; i++) { mbar_init(sb + B_FFULL + 8 * i, 2); mbar_init(sb + B_FEMPTY + 8 * i, 4); }
    asm volatile("fence.mbarrier_init.release.cluster;" ::: "memory");
  } else if (tid == 448) {
    asm volatile("prefetch.tensormap [%0];" ::"l"(&mp.wg) : "memory");
    asm volatile("prefetch.tensormap [%0];" ::"l"(&mp.wu) : "memory");
    asm volatile("prefetch.tensormap [%0];" ::"l"(&mp.wd) : "memory");
    asm volatile("prefetch.tensormap [%0];" ::"l"(&mp.wo) : "memory");
    asm volatile("prefetch.tensormap [%0];" ::"l"(&mp.out) : "memory");
  }
  if (tid < 128) { sts32(sb + ONES_OFF + tid * 4, 0x3F803F80u); asm volatile("fence.proxy.async.shared::cta;" ::: "memory"); }
  __syncthreads();
  if (tid == 0) EV(1);

  uint8_t* const a_tb = g_a + (size_t)(tb * 2) * A_BYTES;
  uint32_t* const fl_tb = g_flags + 64 + tb * 128;

  if (wg == 3) {
    asm volatile("setmaxnreg.dec.sync.aligned.u32 %0;" ::"n"(REG_PROD));
    if (wq4 == 0) {
#pragma unroll 1
      for (int n = 0; n < 32; n++) {
        const int s = n & 3;
        const int hc = n < 24 ? (n & 24) + cg : 24 + (cg >> 1);
        mbar_wait_sleep<NS_W>(sb + B_WEMPTY + 8 * s, (n >> 2) & 1);
        u_tma2d_pair(sb + B_WFULL + 8 * s, sb + W_OFF + s * 16384, &mp.wg, &mp.wu, hc * 64, (n & 7) * 64, (n & 7) * 64);
        if (n == 8) { u_prefetch(wd_raw + blockIdx.x * 14336, 14336); u_prefetch(wo_raw + blockIdx.x * 4096, 4096); }
      }
      mbar_wait_sleep<NS_W>(sb + B_FFN1, 0);
#pragma unroll 1
      for (int n = 0; n < 36; n++) {
        const int s = n & 7;
        mbar_wait_sleep<NS_W>(sb + B_FEMPTY + 8 * s, ((n >> 3) & 1) ^ 1);
        u_tma3d(sb + B_FFULL + 8 * s, 16384, sb + s * FST + 8192, n < 28 ? &mp.wd : &mp.wo, 0, (n < 28 ? n : n - 28) * 64, cg & 6);
      }
    } else if (wq4 == 1) {
      uint64_t f;
      for (int i = 0;; i++) {
        f = ld_acq64(g_flags + 2 * lane);
        if (__all_sync(~0u, (uint32_t)f != 0 && (f >> 32) != 0)) break;
        if (i > 0x100000) __trap();
      }
      const uint32_t fk = __reduce_max_sync(~0u, (uint32_t)f);
      if (lane == 0) { EV(4); sts32(sb + MISC_OFF + 32, fk); }
      fence_async_gl();
      __syncwarp();
#pragma unroll 1
      for (int n = 0; n < 33; n++) {
        const int s = n & 3;
        mbar_wait_sleep<NS_KV>(sb + B_KVEMPTY + 8 * s, ((n >> 2) & 1) ^ 1);
        u_bulk(sb + B_KVFULL + 8 * s, 8192, sb + KV_OFF + s * 8192, g_kv + (n & 15) * 8192);
      }
    } else if (wq4 == 3) {
      if (cg < 4) {
        asm volatile("bar.sync 4, 160;" ::: "memory");
        const uint32_t m = max(max(lds32(sb + MISC_OFF + 48), lds32(sb + MISC_OFF + 52)), max(lds32(sb + MISC_OFF + 56), lds32(sb + MISC_OFF + 60)));
        fence_gpu();
        if (lane == 0) { st_rlx(g_flags + (tb * 2 + half) * 2 + (cg >> 1), m | 1); EV(2); }
      }
#pragma unroll 1
      for (int e = 0; e < 5; e++) {
        mbar_wait_sleep<NS_W>(sb + B_PUB + 8 * e, 0);
        fence_gpu();
        const int idx = e < 3 ? 2 * (e * 8 + cg) : e == 3 ? 2 * (24 + (cg >> 1)) : 2 * cg + 1;
        if (lane < 2 && (e != 3 || lane == half)) st_rlx(fl_tb + lane * 64 + idx, 1);
      }
    } else {
      mbar_wait_sleep<NS_W>(sb + B_FFN1, 0);
      const uint32_t* fl = fl_tb + half * 64 + 2 * lane;
      const uint8_t* src = a_tb + half * A_BYTES;
      int ready = 0;
#pragma unroll 1
      for (int n = 0; n < 36; n++) {
        if (n >= ready) {
          for (int i = 0;; i++) {
            const uint64_t f = ld_acq64(fl);
            const uint32_t rh = __ballot_sync(~0u, (uint32_t)f != 0), ro = __ballot_sync(~0u, (f >> 32) != 0);
            ready = __ffs(~rh) - 1;
            if (ready == 28) ready += (__ffs(~ro) - 1) >> 1;
            if (n < ready) break;
            if (i > 0x100000) __trap();
            __nanosleep(NS_F);
          }
          fence_async_gl();
        }
        const int s = n & 7;
        mbar_wait_sleep<NS_W>(sb + B_FEMPTY + 8 * s, ((n >> 3) & 1) ^ 1);
        u_bulk(sb + B_FFULL + 8 * s, 8192, sb + s * FST, src + n * 8192);
      }
      uint32_t last = 0;
      if (lane == 0) { __threadfence(); last = atomicAdd(&g_done, 1) == gridDim.x - 1; __threadfence(); }
      if (__shfl_sync(~0u, last, 0)) {
        for (int i = lane; i < (64 + 32 * 64) / 4; i += 32) reinterpret_cast<uint4*>(g_flags)[i] = make_uint4(0, 0, 0, 0);
        if (lane == 0) g_done = 0;
      }
    }
  } else if (wg == 2) {
    asm volatile("setmaxnreg.inc.sync.aligned.u32 %0;" ::"n"(REG_GEMM));
    float d0[64], d1[64];
    zero(d0); zero(d1);
    const uint32_t xl = dlo(sb + X_OFF, 16), wl = dlo(sb + W_OFF, 8192);
    constexpr uint32_t H128 = dhi(1024, 1);
    uint8_t* const hdst = a_tb + wq4 * 256 + lane * 4;
    const uint32_t grow = sb + G_OFF + (wq4 * 16 + (lane >> 2)) * 4;
#pragma unroll 1
    for (int st = 0; st < 3; st++) {
#pragma unroll 1
      for (int kc = 0; kc < 8; kc++) {
        const int s = kc & 3;
        if (st == 0) { mbar_wait(sb + B_XFULL + 8 * (kc >> 1), 0); mbar_wait(sb + B_XFULL + 32 + 8 * (kc >> 1), 0); }
        mbar_wait(sb + B_WFULL + 8 * s, (kc >> 2) & 1);
        const uint32_t a = xl + kc * 512, b = wl + s * 1024;
#pragma unroll
        for (int k = 0; k < 4; k++) {
          wg_fence();
          mma_ss_t128(d0, mk64(a + 2 * k, H128), mk64(b + 128 * k, H128), (kc | k) != 0);
          mma_ss_t128(d1, mk64(a + 4096 + 2 * k, H128), mk64(b + 128 * k, H128), (kc | k) != 0);
          wg_commit(); wg_wait<GW1>();
          if (GW1 && k == 0 && kc != 0 && lane == 0) mbar_arrive2(sb + B_WEMPTY + 8 * ((s + 3) & 3));
        }
        if (!GW1 && lane == 0) mbar_arrive2(sb + B_WEMPTY + 8 * s);
      }
      if (GW1) { wg_wait<0>(); if (lane == 0) mbar_arrive2(sb + B_WEMPTY + 8 * 3); }
      pin(d0); pin(d1);
      if (st == 0) { if (tid == 256) EV(8); mbar_wait(sb + B_GREADY, 0); }
      const int hc = st * 8 + cg;
      store_h(d0, __uint_as_float(lds32(grow)), __uint_as_float(lds32(grow + 32)), hdst + hc * 8192);
      store_h(d1, __uint_as_float(lds32(grow + 256)), __uint_as_float(lds32(grow + 288)), hdst + A_BYTES + hc * 8192);
      __syncwarp();
      if (lane == 0) mbar_arrive(sb + B_PUB + 8 * st);
      pin(d0); pin(d1);
    }
    {
#pragma unroll 1
      for (int kc = 0; kc < 8; kc++) {
        const int s = kc & 3;
        mbar_wait(sb + B_WFULL + 8 * s, (kc >> 2) & 1);
        const uint32_t a = xl + kc * 512 + half * 4096, b = wl + s * 1024;
#pragma unroll
        for (int k = 0; k < 4; k += 2) {
          wg_fence();
          mma_ss_t128(d0, mk64(a + 2 * k, H128), mk64(b + 128 * k, H128), (kc | k) != 0);
          mma_ss_t128(d0, mk64(a + 2 * k + 2, H128), mk64(b + 128 * k + 128, H128), 1);
          wg_commit(); wg_wait<GW1>();
          if (GW1 && k == 0 && kc != 0 && lane == 0) mbar_arrive2(sb + B_WEMPTY + 8 * ((s + 3) & 3));
        }
        if (!GW1 && lane == 0) mbar_arrive2(sb + B_WEMPTY + 8 * s);
      }
      wg_wait<0>();
      pin(d0);
      if (lane == 0) mbar_arrive(sb + B_FFN1);
      if (tid == 256) EV(12);
      const int hc = 24 + (cg >> 1);
      store_h(d0, __uint_as_float(lds32(grow + half * 256)), __uint_as_float(lds32(grow + half * 256 + 32)), hdst + half * A_BYTES + hc * 8192);
      __syncwarp();
      if (lane == 0) mbar_arrive(sb + B_PUB + 24);
      pin(d0);
    }
    const uint32_t al = dlo(sb, 1024), bl = dlo(sb + 8192, 8192);
    constexpr uint32_t HA = dhi(128, 0);
#pragma unroll 1
    for (int n = 0; n < 36; n++) {
      const int s = n & 7;
      mbar_wait_sleep<NS_G>(sb + B_FFULL + 8 * s, (n >> 3) & 1);
      const uint32_t a = al + s * (FST >> 4), b = bl + s * (FST >> 4);
#pragma unroll
      for (int k = 0; k < 4; k += 2) {
        wg_fence();
        mma_ss_t128(d0, mk64(a + 128 * k, HA), mk64(b + 128 * k, H128), (n | k) != 0);
        mma_ss_t128(d0, mk64(a + 128 * k + 128, HA), mk64(b + 128 * k + 128, H128), 1);
        wg_commit(); wg_wait<GW2>();
        if (GW2 && k == 0 && n != 0 && lane == 0) mbar_arrive(sb + B_FEMPTY + 8 * ((s + 7) & 7));
      }
      if (!GW2 && lane == 0) mbar_arrive(sb + B_FEMPTY + 8 * s);
    }
    wg_wait<0>();
    pin(d0);
    if (tid == 256) EV(19);
    const uint32_t stg = sb + 4 * FST;
    const int r = wq4 * 16 + (lane & 7) + ((lane >> 3) & 1) * 8;
#pragma unroll
    for (int j = 0; j < 8; j++) {
      const int c16 = (2 * j + (lane >> 4)) & 7;
      const uint32_t ad = stg + (j >> 2) * 8192 + r * 128 + ((c16 ^ (r & 7)) << 4);
      asm volatile("stmatrix.sync.aligned.m8n8.x4.shared.b16 [%0], {%1,%2,%3,%4};" ::"r"(ad), "r"(pack2(d0[8 * j], d0[8 * j + 1])), "r"(pack2(d0[8 * j + 2], d0[8 * j + 3])),
                   "r"(pack2(d0[8 * j + 4], d0[8 * j + 5])), "r"(pack2(d0[8 * j + 6], d0[8 * j + 7])) : "memory");
    }
    asm volatile("fence.proxy.async.shared::cta;" ::: "memory");
    bar_sync(3);
    if (tid == 256) {
      asm volatile("cp.async.bulk.tensor.3d.global.shared::cta.bulk_group [%0, {%2, %3, %4}], [%1];" ::"l"(&mp.out), "r"(stg), "r"(0), "r"(tb * 128 + half * 64), "r"(cg & 6) : "memory");
      asm volatile("cp.async.bulk.commit_group;" ::: "memory");
      asm volatile("cp.async.bulk.wait_group.read 0;" ::: "memory");
      EV(20);
    }
  } else {
    asm volatile("setmaxnreg.inc.sync.aligned.u32 %0;" ::"n"(REG_ATT));
    constexpr uint32_t H128 = dhi(1024, 1);
    const uint32_t xl = dlo(sb + X_OFF + wg * 65536, 16);
    if (cg < 4 && wg == half) {
      float d[8];
      zero(d);
      mbar_wait(sb + B_WKV, 0);
      const uint32_t wl = dlo(sb + KV_OFF, 16);
#pragma unroll 1
      for (int j = 0; j < 4; j++) {
        mbar_wait(sb + B_XFULL + 32 * wg + 8 * j, 0);
        wg_fence();
#pragma unroll
        for (int k = 0; k < 8; k++) mma_ss_t16(d, mk64(xl + j * 1024 + (k >> 2) * 512 + 2 * (k & 3), H128), KD(wl + j * 256 + 32 * k), 1);
        wg_commit();
      }
      wg_wait<0>(); pin(d);
      const uint32_t p0 = pack2(d[0], d[1]), p1 = pack2(d[2], d[3]), p2 = pack2(d[4], d[5]), p3 = pack2(d[6], d[7]);
      const int r = lane >> 2;
      uint8_t* dst = g_kv + (tb * 2 + wg) * 4096 + (cg >> 1) * 2048 + (wq4 * 16 + r) * 32 + (lane & 3) * 4;
      const int sw = (r >> 2) * 16;
      stg32(dst + sw, p0); stg32(dst + 256 + sw, p1); stg32(dst + (sw ^ 16), p2); stg32(dst + 256 + (sw ^ 16), p3);
      float n0 = sqsum2(p0) + sqsum2(p2), n1 = sqsum2(p1) + sqsum2(p3);
      n0 += __shfl_xor_sync(~0u, n0, 1); n1 += __shfl_xor_sync(~0u, n1, 1);
      n0 += __shfl_xor_sync(~0u, n0, 2); n1 += __shfl_xor_sync(~0u, n1, 2);
      const uint32_t mx = __reduce_max_sync(~0u, max(__float_as_uint(n0), __float_as_uint(n1)));
      if (lane == 0) sts32(sb + MISC_OFF + 48 + wq4 * 4, mx);
      asm volatile("bar.arrive 4, 160;" ::: "memory");
    }
    uint32_t q[4][4];
    float g0, g1;
    {
      float d[32], e[4];
      zero(d); zero(e);
      const uint32_t wl = dlo(sb + W_OFF, 8192), gl = dlo(sb + GW_OFF, 16);
#pragma unroll 1
      for (int s = 0; s < 4; s++) {
        mbar_wait(sb + B_XFULL + 32 * wg + 8 * s, 0);
        mbar_wait(sb + B_WQ + 8 * s, 0);
        wg_fence();
#pragma unroll
        for (int k = 0; k < 8; k++) mma_ss_t64(d, mk64(xl + (2 * s + (k >> 2)) * 512 + 2 * (k & 3), H128), mk64(wl + s * 1024 + 64 * k, dhi(512, 2)), 1);
        wg_commit(); wg_wait<0>();
        if (lane == 0) mbar_arrive(sb + B_WEMPTY + 8 * s);
      }
      pin(d);
      wg_fence();
#pragma unroll
      for (int k = 0; k < 32; k++) mma_ss_n8(e, mk64(xl + (k >> 2) * 512 + 2 * (k & 3), H128), mk64(gl + 2 * k, dhi(128, 0)), 1);
      wg_commit();
      constexpr float QS = 0.25f * 1.4426950408889634f;
      float nm = 0.f;
#pragma unroll
      for (int h = 0; h < 4; h++) {
#pragma unroll
        for (int i = 0; i < 4; i++) q[h][i] = pack2(d[8 * h + 2 * i] * QS, d[8 * h + 2 * i + 1] * QS);
        float n0 = sqsum2(q[h][0]) + sqsum2(q[h][2]), n1 = sqsum2(q[h][1]) + sqsum2(q[h][3]);
        n0 += __shfl_xor_sync(~0u, n0, 1); n1 += __shfl_xor_sync(~0u, n1, 1);
        n0 += __shfl_xor_sync(~0u, n0, 2); n1 += __shfl_xor_sync(~0u, n1, 2);
        nm = __uint_as_float(max(__float_as_uint(nm), max(__float_as_uint(n0), __float_as_uint(n1))));
      }
      const uint32_t mx = __reduce_max_sync(~0u, __float_as_uint(nm));
      if (lane == 0) sts32(sb + MISC_OFF + warp * 4, mx);
      wg_wait<0>(); pin(e);
      const float z0 = __shfl_sync(~0u, e[0], lane & ~3), z1 = __shfl_sync(~0u, e[2], lane & ~3);
      g0 = 1.f / (1.f + __expf(-z0)); g1 = 1.f / (1.f + __expf(-z1));
      if ((lane & 3) == 0) {
        const uint32_t ga = sb + G_OFF + (wg * 64 + wq4 * 16 + (lane >> 2)) * 4;
        sts32(ga, __float_as_uint(0.5f * (1.f - g0))); sts32(ga + 32, __float_as_uint(0.5f * (1.f - g1)));
      }
      __syncwarp();
      if (lane == 0) mbar_arrive(sb + B_GREADY);
    }
    bar_sync(1 + wg);
    if (tid == 0) EV(3);
    const uint32_t qa = sb + MISC_OFF + wg * 16;
    const float qm = __uint_as_float(max(max(lds32(qa), lds32(qa + 4)), max(lds32(qa + 8), lds32(qa + 12))));
    mbar_wait(sb + B_KVFULL, 0);
    if (tid == 0) EV(5);
    const float km = __uint_as_float(lds32(sb + MISC_OFF + 32));
    const bool fast = !FORCE_SLOW && (qm * km <= 930.f);
    const uint32_t one = lds32(sb + ONES_OFF) & 0x3C003C00u;
    uint8_t* odst = a_tb + wg * A_BYTES + (224 + cg * 4) * 1024 + wq4 * 256 + lane * 4;
    uint32_t* const oflag = fl_tb + wg * 64 + 2 * (8 + cg) + 1;
    if (fast) attn_passes<true>(q, g0, g1, odst, oflag, wg, one);
    else attn_passes<false>(q, g0, g1, odst, oflag, wg, one);
  }
}

typedef CUresult (*EncodeFn)(CUtensorMap*, CUtensorMapDataType, cuuint32_t, void*, const cuuint64_t*, const cuuint64_t*, const cuuint32_t*, const cuuint32_t*,
                             CUtensorMapInterleave, CUtensorMapSwizzle, CUtensorMapL2promotion, CUtensorMapFloatOOBfill);

void make_map(EncodeFn fn, CUtensorMap* m, const void* p, uint64_t cols, uint64_t rows, uint32_t bc, uint32_t br, CUtensorMapSwizzle sw) {
  cuuint64_t dims[2] = {cols, rows}, strides[1] = {cols * 2};
  cuuint32_t box[2] = {bc, br}, es[2] = {1, 1};
  fn(m, CU_TENSOR_MAP_DATA_TYPE_BFLOAT16, 2, const_cast<void*>(p), dims, strides, box, es, CU_TENSOR_MAP_INTERLEAVE_NONE, sw,
     CU_TENSOR_MAP_L2_PROMOTION_L2_128B, CU_TENSOR_MAP_FLOAT_OOB_FILL_NONE);
}

void make_map3(EncodeFn fn, CUtensorMap* m, const void* p, uint64_t bw, uint64_t nblk, uint64_t rows, uint32_t bc, uint32_t br, CUtensorMapSwizzle sw) {
  cuuint64_t dims[3] = {bw, rows, nblk}, strides[2] = {bw * nblk * 2, bw * 2};
  cuuint32_t box[3] = {bc, br, 2}, es[3] = {1, 1, 1};
  fn(m, CU_TENSOR_MAP_DATA_TYPE_BFLOAT16, 3, const_cast<void*>(p), dims, strides, box, es, CU_TENSOR_MAP_INTERLEAVE_NONE, sw,
     CU_TENSOR_MAP_L2_PROMOTION_L2_128B, CU_TENSOR_MAP_FLOAT_OOB_FILL_NONE);
}

}

extern "C" void kernel_launch(void* const* d_in, const int* in_sizes, int n_in, void* d_out, int out_size) {
  void* fp = nullptr;
  cudaDriverEntryPointQueryResult qr;
  cudaGetDriverEntryPoint("cuTensorMapEncodeTiled", &fp, cudaEnableDefault, &qr);
  EncodeFn fn = (EncodeFn)fp;
  Maps mp;
  make_map3(fn, &mp.x, d_in[0], 64, 8, S_, 64, 64, CU_TENSOR_MAP_SWIZZLE_128B);
  make_map3(fn, &mp.wq, d_in[1], 256, 2, D_, 32, 128, CU_TENSOR_MAP_SWIZZLE_64B);
  make_map(fn, &mp.wk, d_in[2], 16, D_, 16, 256, CU_TENSOR_MAP_SWIZZLE_32B);
  make_map(fn, &mp.wv, d_in[3], 16, D_, 16, 256, CU_TENSOR_MAP_SWIZZLE_32B);
  make_map3(fn, &mp.wo, d_in[4], 64, 8, D_, 64, 64, CU_TENSOR_MAP_SWIZZLE_128B);
  make_map(fn, &mp.wg, d_in[6], F_, D_, 64, 64, CU_TENSOR_MAP_SWIZZLE_128B);
  make_map(fn, &mp.wu, d_in[7], F_, D_, 64, 64, CU_TENSOR_MAP_SWIZZLE_128B);
  make_map3(fn, &mp.wd, d_in[8], 64, 8, F_, 64, 64, CU_TENSOR_MAP_SWIZZLE_128B);
  make_map3(fn, &mp.out, d_out, 64, 8, S_, 64, 64, CU_TENSOR_MAP_SWIZZLE_128B);
  cudaFuncSetAttribute(fused_kernel, cudaFuncAttributeMaxDynamicSharedMemorySize, SMEM_BYTES);
  fused_kernel<<<128, 512, SMEM_BYTES, cudaStreamPerThread>>>(mp, (const __nv_bfloat16*)d_in[9], (const uint8_t*)d_in[8], (const uint8_t*)d_in[4]);
}
```

```cpp
#include <cuda_runtime.h>
#include <cuda_bf16.h>
#include <cuda.h>
#include <stdint.h>

#define DEG 2
#define REG_ATT 160
#define REG_GEMM 160
#define REG_PROD 32
#define FORCE_SLOW 0
#define NS_W 100
#define NS_KV 200
#define NS_F 200
#define NS_G 50
#define GW1 0
#define GW2 1
#define HINT 4000
#define EXP 0

namespace {

constexpr int S_ = 2048, D_ = 512, F_ = 1792;
constexpr float QS = 0.25f * 1.4426950408889634f;

constexpr uint32_t sb = 1024;
constexpr uint32_t X_OFF = 0;
constexpr uint32_t W_OFF = 131072;
constexpr uint32_t KV_OFF = 196608;
constexpr uint32_t ONES_OFF = 229376;
constexpr uint32_t GW_OFF = 229888;
constexpr uint32_t G_OFF = 231040;
constexpr uint32_t MISC_OFF = 231552;
constexpr uint32_t BAR_OFF = 231616;
constexpr uint32_t B_XFULL = BAR_OFF;
constexpr uint32_t B_PUB = B_XFULL + 64;
constexpr uint32_t B_WKV = B_XFULL + 128;
constexpr uint32_t B_GREADY = B_WKV + 8;
constexpr uint32_t B_FFN1 = B_GREADY + 8;
constexpr uint32_t B_WFULL = B_FFN1 + 8;
constexpr uint32_t B_WEMPTY = B_WFULL + 32;
constexpr uint32_t B_KVFULL = B_WEMPTY + 32;
constexpr uint32_t B_KVEMPTY = B_KVFULL + 32;
constexpr uint32_t B_FFULL = B_KVEMPTY + 32;
constexpr uint32_t B_FEMPTY = B_FFULL + 64;
constexpr uint32_t B_WQ = B_FEMPTY + 64;
constexpr uint32_t SMEM_BYTES = B_WQ + 32;
constexpr uint32_t FST = 24576;
static_assert(SMEM_BYTES <= 232448, "smem");

constexpr int A_BYTES = 288 * 1024;
__device__ __align__(1024) uint8_t g_kv[32 * 4096];
__device__ uint4 g_kvb[128 * 64];
__device__ __align__(1024) uint8_t g_a[32 * A_BYTES];
__device__ __align__(256) uint32_t g_flags[64 + 32 * 64];
__device__ uint32_t g_done;

#define EV(i)
#define EVC(i)
struct Maps { CUtensorMap x, wq, wk, wv, wo, wg, wu, wd, out; };

__device__ __forceinline__ void wg_fence() { asm volatile("wgmma.fence.sync.aligned;" ::: "memory"); }
__device__ __forceinline__ void wg_commit() { asm volatile("wgmma.commit_group.sync.aligned;" ::: "memory"); }
template <int N> __device__ __forceinline__ void wg_wait() { asm volatile("wgmma.wait_group.sync.aligned %0;" ::"n"(N) : "memory"); }
template <int N> __device__ __forceinline__ void pin(float (&d)[N]) {
#pragma unroll
  for (int i = 0; i < N; i++) asm volatile("" : "+f"(d[i])::"memory");
}
template <int N> __device__ __forceinline__ void pinu(uint32_t (&d)[N]) {
#pragma unroll
  for (int i = 0; i < N; i++) asm volatile("" : "+r"(d[i])::"memory");
}
template <int N> __device__ __forceinline__ void zero(float (&d)[N]) {
#pragma unroll
  for (int i = 0; i < N; i++) d[i] = 0.f;
  pin(d);
}
__device__ __forceinline__ uint64_t mk64(uint32_t lo, uint32_t hi) { return ((uint64_t)hi << 32) | lo; }
__host__ __device__ constexpr uint32_t dhi(uint32_t sbo, uint32_t sw) { return (sbo >> 4) | (sw << 30); }
__device__ __forceinline__ uint32_t dlo(uint32_t addr, uint32_t lbo) { return (addr >> 4) | ((lbo >> 4) << 16); }

__device__ __forceinline__ void mbar_init(uint32_t b, uint32_t n) { asm volatile("mbarrier.init.shared::cta.b64 [%0], %1;" ::"r"(b), "r"(n) : "memory"); }
__device__ __forceinline__ void mbar_arrive(uint32_t b) { asm volatile("mbarrier.arrive.shared::cta.b64 _, [%0];" ::"r"(b) : "memory"); }
__device__ __forceinline__ void mbar_arrive2(uint32_t b) { asm volatile("mbarrier.arrive.shared::cta.b64 _, [%0], 2;" ::"r"(b) : "memory"); }
__device__ __forceinline__ void mbar_expect(uint32_t b, uint32_t bytes) { asm volatile("mbarrier.arrive.expect_tx.shared::cta.b64 _, [%0], %1;" ::"r"(b), "r"(bytes) : "memory"); }
__device__ __forceinline__ void mbar_wait(uint32_t b, uint32_t parity) {
  asm volatile(
      "{\n.reg .pred p;\n.reg .u32 c;\n"
      "mbarrier.try_wait.parity.shared::cta.b64 p, [%0], %1;\n"
      "@p bra DONE;\n"
      "mov.u32 c, 0;\n"
      "SPIN:\n"
      "mbarrier.try_wait.parity.shared::cta.b64 p, [%0], %1;\n"
      "@p bra DONE;\n"
      "add.u32 c, c, 1;\n"
      "setp.lt.u32 p, c, 0x100000;\n"
      "@p bra SPIN;\n"
      "trap;\n"
      "DONE:\n}\n" ::"r"(b), "r"(parity) : "memory");
}
template <int NS> __device__ __forceinline__ void mbar_wait_sleep(uint32_t b, uint32_t parity) {
  asm volatile(
      "{\n.reg .pred p;\n.reg .u32 c;\n"
      "mov.u32 c, 0;\n"
      "SPIN:\n"
      "mbarrier.try_wait.parity.shared::cta.b64 p, [%0], %1, %2;\n"
      "@p bra.uni DONE;\n"
      "add.u32 c, c, 1;\n"
      "setp.lt.u32 p, c, 0x40000;\n"
      "@p bra.uni SPIN;\n"
      "trap;\n"
      "DONE:\n}\n" ::"r"(b), "r"(parity), "n"(HINT) : "memory");
  return;
  asm volatile(
      "{\n.reg .pred p;\n.reg .u32 c;\n"
      "mov.u32 c, 0;\n"
      "SPIN:\n"
      "mbarrier.test_wait.parity.shared::cta.b64 p, [%0], %1;\n"
      "@p bra.uni DONE;\n"
      "nanosleep.u32 %2;\n"
      "add.u32 c, c, 1;\n"
      "setp.lt.u32 p, c, 0x100000;\n"
      "@p bra.uni SPIN;\n"
      "trap;\n"
      "DONE:\n}\n" ::"r"(b), "r"(parity), "n"(NS) : "memory");
}
#define ELECT "{\n.reg .pred p;\nelect.sync _|p, 0xffffffff;\n@p mbarrier.arrive.expect_tx.shared::cta.b64 _, [%0], %1;\n"
__device__ __forceinline__ void u_tma3d(uint32_t bar, uint32_t bytes, uint32_t dst, const CUtensorMap* m, int c0, int c1, int c2) {
  asm volatile(ELECT "@p cp.async.bulk.tensor.3d.shared::cluster.global.mbarrier::complete_tx::bytes [%2], [%3, {%4, %5, %6}], [%0];\n}\n" ::"r"(bar), "r"(bytes), "r"(dst), "l"(m), "r"(c0), "r"(c1), "r"(c2) : "memory");
}
__device__ __forceinline__ void u_tma2d_pair(uint32_t bar, uint32_t dst, const CUtensorMap* m0, const CUtensorMap* m1, int c0, int c1, int c1b) {
  asm volatile(ELECT "@p cp.async.bulk.tensor.2d.shared::cluster.global.mbarrier::complete_tx::bytes [%2], [%3, {%5, %6}], [%0];\n"
               "@p cp.async.bulk.tensor.2d.shared::cluster.global.mbarrier::complete_tx::bytes [%2 + 8192], [%4, {%5, %7}], [%0];\n}\n" ::"r"(bar), "r"(16384), "r"(dst), "l"(m0), "l"(m1), "r"(c0), "r"(c1), "r"(c1b) : "memory");
}
__device__ __forceinline__ void u_bulk(uint32_t bar, uint32_t bytes, uint32_t dst, const void* src) {
  asm volatile(ELECT "@p cp.async.bulk.shared::cluster.global.mbarrier::complete_tx::bytes [%2], [%3], %1, [%0];\n}\n" ::"r"(bar), "r"(bytes), "r"(dst), "l"(src) : "memory");
}
__device__ __forceinline__ void u_prefetch(const void* src, uint32_t bytes) {
  asm volatile("{\n.reg .pred p;\nelect.sync _|p, 0xffffffff;\n@p cp.async.bulk.prefetch.L2.global [%0], %1;\n}\n" ::"l"(src), "r"(bytes) : "memory");
}
__device__ __forceinline__ void fence_gpu() { asm volatile("fence.acq_rel.gpu;" ::: "memory"); }
__device__ __forceinline__ void st_rlx(uint32_t* p, uint32_t v) { asm volatile("st.relaxed.gpu.global.u32 [%0], %1;" ::"l"(p), "r"(v) : "memory"); }
__device__ __forceinline__ uint64_t ld_acq64(const uint32_t* p) { uint64_t v; asm volatile("ld.acquire.gpu.global.u64 %0, [%1];" : "=l"(v) : "l"(p) : "memory"); return v; }
__device__ __forceinline__ void tma2d(uint32_t dst, const CUtensorMap* m, int c0, int c1, uint32_t bar) {
  asm volatile("cp.async.bulk.tensor.2d.shared::cluster.global.mbarrier::complete_tx::bytes [%0], [%1, {%3, %4}], [%2];" ::"r"(dst), "l"(m), "r"(bar), "r"(c0), "r"(c1) : "memory");
}
__device__ __forceinline__ void bulk_ld(uint32_t dst, const void* src, uint32_t bytes, uint32_t bar) {
  asm volatile("cp.async.bulk.shared::cluster.global.mbarrier::complete_tx::bytes [%0], [%1], %2, [%3];" ::"r"(dst), "l"(src), "r"(bytes), "r"(bar) : "memory");
}
__device__ __forceinline__ void l2_prefetch(const void* src, uint32_t bytes) {
  asm volatile("cp.async.bulk.prefetch.L2.global [%0], %1;" ::"l"(src), "r"(bytes) : "memory");
}
__device__ __forceinline__ uint32_t ld_acq(const uint32_t* p) { uint32_t v; asm volatile("ld.acquire.gpu.global.u32 %0, [%1];" : "=r"(v) : "l"(p) : "memory"); return v; }
__device__ __forceinline__ void st_rel(uint32_t* p, uint32_t v) { asm volatile("st.release.gpu.global.u32 [%0], %1;" ::"l"(p), "r"(v) : "memory"); }
__device__ __forceinline__ void fence_async_all() { asm volatile("fence.proxy.async;" ::: "memory"); }
__device__ __forceinline__ void fence_async_gl() { asm volatile("fence.proxy.async.global;" ::: "memory"); }
__device__ __forceinline__ void bar_sync(int id) { asm volatile("bar.sync %0, 128;" ::"r"(id) : "memory"); }
__device__ __forceinline__ uint32_t pack2(float lo, float hi) { uint32_t r; asm("cvt.rn.bf16x2.f32 %0, %1, %2;" : "=r"(r) : "f"(hi), "f"(lo)); return r; }
__device__ __forceinline__ float ex2(float a) { float r; asm("ex2.approx.ftz.f32 %0, %1;" : "=f"(r) : "f"(a)); return r; }
__device__ __forceinline__ float sq4(float a, float b, float c, float d) { return fmaf(a, a, b * b) + fmaf(c, c, d * d); }
__device__ __forceinline__ void stg32(void* p, uint32_t v) { asm volatile("st.global.u32 [%0], %1;" ::"l"(p), "r"(v) : "memory"); }
__device__ __forceinline__ void sts32(uint32_t a, uint32_t v) { asm volatile("st.shared.u32 [%0], %1;" ::"r"(a), "r"(v) : "memory"); }
__device__ __forceinline__ uint32_t lds32(uint32_t a) { uint32_t v; asm volatile("ld.shared.u32 %0, [%1];" : "=r"(v) : "r"(a) : "memory"); return v; }

__device__ __forceinline__ void mma_qk(uint32_t (&d)[16], const uint32_t (&a)[4], uint64_t b) {
  asm volatile("{\n.reg .pred p;\nsetp.ne.b32 p, 0, 0;\n"
    "wgmma.mma_async.sync.aligned.m64n64k16.f16.f16.f16 {%0,%1,%2,%3,%4,%5,%6,%7,%8,%9,%10,%11,%12,%13,%14,%15}, {%16,%17,%18,%19}, %20, p, 1, 1, 0;\n}\n"
    : "+r"(d[0]),"+r"(d[1]),"+r"(d[2]),"+r"(d[3]),"+r"(d[4]),"+r"(d[5]),"+r"(d[6]),"+r"(d[7]),"+r"(d[8]),"+r"(d[9]),"+r"(d[10]),"+r"(d[11]),"+r"(d[12]),"+r"(d[13]),"+r"(d[14]),"+r"(d[15]) : "r"(a[0]),"r"(a[1]),"r"(a[2]),"r"(a[3]),"l"(b));
}
__device__ __forceinline__ void mma_pv(float (&d)[12], const uint32_t (&a)[4], uint64_t b) {
  asm volatile("{\n.reg .pred p;\nsetp.ne.b32 p, 1, 0;\n"
    "wgmma.mma_async.sync.aligned.m64n24k16.f32.f16.f16 {%0,%1,%2,%3,%4,%5,%6,%7,%8,%9,%10,%11}, {%12,%13,%14,%15}, %16, p, 1, 1, 1;\n}\n"
    : "+f"(d[0]),"+f"(d[1]),"+f"(d[2]),"+f"(d[3]),"+f"(d[4]),"+f"(d[5]),"+f"(d[6]),"+f"(d[7]),"+f"(d[8]),"+f"(d[9]),"+f"(d[10]),"+f"(d[11]) : "r"(a[0]),"r"(a[1]),"r"(a[2]),"r"(a[3]),"l"(b));
}
__device__ __forceinline__ void mma_ss_t128(float (&d)[64], uint64_t a, uint64_t b, int acc) {
  asm volatile("{\n.reg .pred p;\nsetp.ne.b32 p, %66, 0;\n"
    "wgmma.mma_async.sync.aligned.m64n128k16.f32.bf16.bf16 {%0,%1,%2,%3,%4,%5,%6,%7,%8,%9,%10,%11,%12,%13,%14,%15,%16,%17,%18,%19,%20,%21,%22,%23,%24,%25,%26,%27,%28,%29,%30,%31,%32,%33,%34,%35,%36,%37,%38,%39,%40,%41,%42,%43,%44,%45,%46,%47,%48,%49,%50,%51,%52,%53,%54,%55,%56,%57,%58,%59,%60,%61,%62,%63}, %64, %65, p, 1, 1, 0, 1;\n}\n"
    : "+f"(d[0]),"+f"(d[1]),"+f"(d[2]),"+f"(d[3]),"+f"(d[4]),"+f"(d[5]),"+f"(d[6]),"+f"(d[7]),"+f"(d[8]),"+f"(d[9]),"+f"(d[10]),"+f"(d[11]),"+f"(d[12]),"+f"(d[13]),"+f"(d[14]),"+f"(d[15]),"+f"(d[16]),"+f"(d[17]),"+f"(d[18]),"+f"(d[19]),"+f"(d[20]),"+f"(d[21]),"+f"(d[22]),"+f"(d[23]),"+f"(d[24]),"+f"(d[25]),"+f"(d[26]),"+f"(d[27]),"+f"(d[28]),"+f"(d[29]),"+f"(d[30]),"+f"(d[31]),"+f"(d[32]),"+f"(d[33]),"+f"(d[34]),"+f"(d[35]),"+f"(d[36]),"+f"(d[37]),"+f"(d[38]),"+f"(d[39]),"+f"(d[40]),"+f"(d[41]),"+f"(d[42]),"+f"(d[43]),"+f"(d[44]),"+f"(d[45]),"+f"(d[46]),"+f"(d[47]),"+f"(d[48]),"+f"(d[49]),"+f"(d[50]),"+f"(d[51]),"+f"(d[52]),"+f"(d[53]),"+f"(d[54]),"+f"(d[55]),"+f"(d[56]),"+f"(d[57]),"+f"(d[58]),"+f"(d[59]),"+f"(d[60]),"+f"(d[61]),"+f"(d[62]),"+f"(d[63]) : "l"(a),"l"(b),"r"(acc));
}
__device__ __forceinline__ void mma_ss_t64(float (&d)[32], uint64_t a, uint64_t b, int acc) {
  asm volatile("{\n.reg .pred p;\nsetp.ne.b32 p, %34, 0;\n"
    "wgmma.mma_async.sync.aligned.m64n64k16.f32.bf16.bf16 {%0,%1,%2,%3,%4,%5,%6,%7,%8,%9,%10,%11,%12,%13,%14,%15,%16,%17,%18,%19,%20,%21,%22,%23,%24,%25,%26,%27,%28,%29,%30,%31}, %32, %33, p, 1, 1, 0, 1;\n}\n"
    : "+f"(d[0]),"+f"(d[1]),"+f"(d[2]),"+f"(d[3]),"+f"(d[4]),"+f"(d[5]),"+f"(d[6]),"+f"(d[7]),"+f"(d[8]),"+f"(d[9]),"+f"(d[10]),"+f"(d[11]),"+f"(d[12]),"+f"(d[13]),"+f"(d[14]),"+f"(d[15]),"+f"(d[16]),"+f"(d[17]),"+f"(d[18]),"+f"(d[19]),"+f"(d[20]),"+f"(d[21]),"+f"(d[22]),"+f"(d[23]),"+f"(d[24]),"+f"(d[25]),"+f"(d[26]),"+f"(d[27]),"+f"(d[28]),"+f"(d[29]),"+f"(d[30]),"+f"(d[31]) : "l"(a),"l"(b),"r"(acc));
}
__device__ __forceinline__ void mma_ss_t16(float (&d)[8], uint64_t a, uint64_t b, int acc) {
  asm volatile("{\n.reg .pred p;\nsetp.ne.b32 p, %10, 0;\n"
    "wgmma.mma_async.sync.aligned.m64n16k16.f32.bf16.bf16 {%0,%1,%2,%3,%4,%5,%6,%7}, %8, %9, p, 1, 1, 0, 1;\n}\n"
    : "+f"(d[0]),"+f"(d[1]),"+f"(d[2]),"+f"(d[3]),"+f"(d[4]),"+f"(d[5]),"+f"(d[6]),"+f"(d[7]) : "l"(a),"l"(b),"r"(acc));
}
__device__ __forceinline__ void mma_ss_n8(float (&d)[4], uint64_t a, uint64_t b, int acc) {
  asm volatile("{\n.reg .pred p;\nsetp.ne.b32 p, %6, 0;\n"
    "wgmma.mma_async.sync.aligned.m64n8k16.f32.bf16.bf16 {%0,%1,%2,%3}, %4, %5, p, 1, 1, 0, 0;\n}\n"
    : "+f"(d[0]),"+f"(d[1]),"+f"(d[2]),"+f"(d[3]) : "l"(a),"l"(b),"r"(acc));
}

__device__ __forceinline__ uint32_t hfma2(uint32_t a, uint32_t b, uint32_t c) { uint32_t r; asm("fma.rn.f16x2 %0, %1, %2, %3;" : "=r"(r) : "r"(a), "r"(b), "r"(c)); return r; }
__device__ __forceinline__ uint32_t packh(float lo, float hi) { uint32_t r; asm("cvt.rn.f16x2.f32 %0, %1, %2;" : "=r"(r) : "f"(hi), "f"(lo)); return r; }
__device__ __forceinline__ uint32_t exp2_mufu(uint32_t s) { uint32_t r; asm("ex2.approx.f16x2 %0, %1;" : "=r"(r) : "r"(s)); return r; }
__device__ __forceinline__ uint32_t exp2_fma(uint32_t s) {
  uint32_t t, u;
  asm("fma.rn.relu.f16x2 %0, %1, %2, %3;" : "=r"(t) : "r"(s), "r"(0x02000200u), "r"(0x000a000au));
  asm("mul.rn.f16x2 %0, %1, %2;" : "=r"(u) : "r"(s), "r"(0x02000200u));
  const uint32_t f = hfma2(u, 0xF800F800u, s);
  const uint32_t y = hfma2(hfma2(f, 0x45614561u, 0x27f627f6u), f, 0x05aa05aau);
  return y + (t << 10);
}
template <int J> __device__ __forceinline__ void sm_unit(const uint32_t (&s)[16], uint32_t (&p)[4]) {
  p[0] = exp2_mufu(s[4 * J]); p[1] = exp2_fma(s[4 * J + 1]); p[2] = exp2_mufu(s[4 * J + 2]); p[3] = exp2_fma(s[4 * J + 3]);
}

#define KD(lo) mk64((lo), dhi(256, 3))
#define VO(x) ((uint32_t)(x) - ((uint32_t)(x) << 16))

__device__ __forceinline__ void attn_fast(const uint32_t (&q0)[4], const uint32_t (&q1)[4], float (&o0)[12], float (&o1)[12], int lane) {
  const uint32_t kvfull = sb + B_KVFULL, kvempty = sb + B_KVEMPTY;
  const uint32_t kbase = dlo(sb + KV_OFF, 16), vbase = dlo(sb + KV_OFF, ONES_OFF - KV_OFF);
  uint32_t s0[16] = {}, s1[16] = {};
  pinu(s0); pinu(s1); zero(o0); zero(o1);
  {
    uint32_t p0[4]={0,0,0,0}; pinu(p0);
    uint32_t p1[4]={0,0,0,0}; pinu(p1);
    uint32_t p2[4]={0,0,0,0}; pinu(p2);
    uint32_t p3[4]={0,0,0,0}; pinu(p3);
    wg_fence(); mma_qk(s0, q0, KD(kbase)); wg_commit(); wg_wait<0>(); pinu(s0);
    uint32_t vprev = vbase - VO(512);
#pragma unroll 1
    for (int it = 0; it < 8; it++) {
      const uint32_t sA = (it & 1) * 2, ph = (it >> 1) & 1, phn = ((it + 1) >> 1) & 1;
      const uint32_t kcur = kbase + sA * 512, knxt = kbase + (sA ^ 2) * 512, vcur = vbase + VO(sA * 512);
      wg_fence();
      mma_qk(s1,q1,KD(kcur+0));
      mma_pv(o1,p2,KD(vprev+VO(960)));
      mma_pv(o1,p3,KD(vprev+VO(992)));
      wg_commit();
      sm_unit<0>(s0,p0);
      sm_unit<1>(s0,p1);
      wg_fence();
      mma_pv(o0,p0,KD(vcur+VO(128)));
      mma_pv(o0,p1,KD(vcur+VO(160)));
      wg_commit();
      wg_wait<1>();
      if (!(EXP & 32) && lane==0 && it!=0) mbar_arrive(kvempty+8*((sA^2)+1));
      sm_unit<2>(s0,p2);
      sm_unit<3>(s0,p3);
      wg_fence();
      mma_qk(s0,q0,KD(kcur+256));
      mma_pv(o0,p2,KD(vcur+VO(192)));
      mma_pv(o0,p3,KD(vcur+VO(224)));
      wg_commit();
      wg_wait<1>(); pinu(s1);
      sm_unit<0>(s1,p0);
      sm_unit<1>(s1,p1);
      wg_fence();
      mma_pv(o1,p0,KD(vcur+VO(128)));
      mma_pv(o1,p1,KD(vcur+VO(160)));
      wg_commit();
      wg_wait<1>();
      sm_unit<2>(s1,p2);
      sm_unit<3>(s1,p3);
      wg_fence();
      mma_qk(s1,q1,KD(kcur+256));
      mma_pv(o1,p2,KD(vcur+VO(192)));
      mma_pv(o1,p3,KD(vcur+VO(224)));
      wg_commit();
      wg_wait<1>(); pinu(s0);
      sm_unit<0>(s0,p0);
      sm_unit<1>(s0,p1);
      wg_fence();
      mma_pv(o0,p0,KD(vcur+VO(384)));
      mma_pv(o0,p1,KD(vcur+VO(416)));
      wg_commit();
      wg_wait<1>();
      sm_unit<2>(s0,p2);
      sm_unit<3>(s0,p3);
      if (!(EXP & 16)) mbar_wait(kvfull+8*(sA+1), ph);
      wg_fence();
      mma_qk(s0,q0,KD(kcur+512));
      mma_pv(o0,p2,KD(vcur+VO(448)));
      mma_pv(o0,p3,KD(vcur+VO(480)));
      wg_commit();
      wg_wait<1>(); pinu(s1);
      sm_unit<0>(s1,p0);
      sm_unit<1>(s1,p1);
      wg_fence();
      mma_pv(o1,p0,KD(vcur+VO(384)));
      mma_pv(o1,p1,KD(vcur+VO(416)));
      wg_commit();
      wg_wait<1>();
      sm_unit<2>(s1,p2);
      sm_unit<3>(s1,p3);
      wg_fence();
      mma_qk(s1,q1,KD(kcur+512));
      mma_pv(o1,p2,KD(vcur+VO(448)));
      mma_pv(o1,p3,KD(vcur+VO(480)));
      wg_commit();
      wg_wait<1>(); pinu(s0);
      sm_unit<0>(s0,p0);
      sm_unit<1>(s0,p1);
      wg_fence();
      mma_pv(o0,p0,KD(vcur+VO(640)));
      mma_pv(o0,p1,KD(vcur+VO(672)));
      wg_commit();
      wg_wait<1>();
      if (!(EXP & 32) && lane==0) mbar_arrive(kvempty+8*sA);
      sm_unit<2>(s0,p2);
      sm_unit<3>(s0,p3);
      wg_fence();
      mma_qk(s0,q0,KD(kcur+768));
      mma_pv(o0,p2,KD(vcur+VO(704)));
      mma_pv(o0,p3,KD(vcur+VO(736)));
      wg_commit();
      wg_wait<1>(); pinu(s1);
      sm_unit<0>(s1,p0);
      sm_unit<1>(s1,p1);
      wg_fence();
      mma_pv(o1,p0,KD(vcur+VO(640)));
      mma_pv(o1,p1,KD(vcur+VO(672)));
      wg_commit();
      wg_wait<1>();
      sm_unit<2>(s1,p2);
      sm_unit<3>(s1,p3);
      wg_fence();
      mma_qk(s1,q1,KD(kcur+768));
      mma_pv(o1,p2,KD(vcur+VO(704)));
      mma_pv(o1,p3,KD(vcur+VO(736)));
      wg_commit();
      wg_wait<1>(); pinu(s0);
      sm_unit<0>(s0,p0);
      sm_unit<1>(s0,p1);
      wg_fence();
      mma_pv(o0,p0,KD(vcur+VO(896)));
      mma_pv(o0,p1,KD(vcur+VO(928)));
      wg_commit();
      wg_wait<1>();
      sm_unit<2>(s0,p2);
      sm_unit<3>(s0,p3);
      if (!(EXP & 16)) mbar_wait(kvfull+8*(sA^2), phn);
      wg_fence();
      mma_qk(s0,q0,KD(knxt));
      mma_pv(o0,p2,KD(vcur+VO(960)));
      mma_pv(o0,p3,KD(vcur+VO(992)));
      wg_commit();
      wg_wait<1>(); pinu(s1);
      sm_unit<0>(s1,p0);
      sm_unit<1>(s1,p1);
      wg_fence();
      mma_pv(o1,p0,KD(vcur+VO(896)));
      mma_pv(o1,p1,KD(vcur+VO(928)));
      wg_commit();
      wg_wait<1>();
      sm_unit<2>(s1,p2);
      sm_unit<3>(s1,p3);
      wg_wait<0>(); pinu(s0); pin(o0); pin(o1);
      vprev = vcur;
    }
    wg_fence();
    mma_pv(o1,p2,KD(vprev+VO(960)));
    mma_pv(o1,p3,KD(vprev+VO(992)));
    wg_commit(); wg_wait<0>(); pin(o0); pin(o1);
    if (lane == 0) mbar_arrive(kvempty + 8 * 3);
  }
}

__device__ __forceinline__ void mma16816(float* d, const uint32_t (&a)[4], uint32_t b0, uint32_t b1) {
  asm("mma.sync.aligned.m16n8k16.row.col.f32.bf16.bf16.f32 {%0,%1,%2,%3}, {%4,%5,%6,%7}, {%8,%9}, {%0,%1,%2,%3};"
      : "+f"(d[0]), "+f"(d[1]), "+f"(d[2]), "+f"(d[3]) : "r"(a[0]), "r"(a[1]), "r"(a[2]), "r"(a[3]), "r"(b0), "r"(b1));
}
__device__ __forceinline__ uint32_t trans8(uint32_t a) { uint32_t r; asm("movmatrix.sync.aligned.m8n8.trans.b16 %0, %1;" : "=r"(r) : "r"(a)); return r; }
__device__ __forceinline__ void attn_online(const uint32_t (&q)[4], float (&o)[12], int lane) {
#pragma unroll
  for (int i = 0; i < 12; i++) o[i] = 0.f;
  float m0 = -3e38f, m1 = -3e38f;
#pragma unroll 2
  for (int b = 0; b < 128; b++) {
    const uint4 k = __ldcg(g_kvb + b * 64 + lane), v = __ldcg(g_kvb + b * 64 + 32 + lane);
    float s[8] = {};
    mma16816(s, q, k.x, k.z); mma16816(s + 4, q, k.y, k.w);
    float x = fmaxf(fmaxf(m0, fmaxf(s[0], s[1])), fmaxf(s[4], s[5])), y = fmaxf(fmaxf(m1, fmaxf(s[2], s[3])), fmaxf(s[6], s[7]));
    x = fmaxf(x, __shfl_xor_sync(~0u, x, 1)); x = fmaxf(x, __shfl_xor_sync(~0u, x, 2));
    y = fmaxf(y, __shfl_xor_sync(~0u, y, 1)); y = fmaxf(y, __shfl_xor_sync(~0u, y, 2));
    const float cx = ex2((m0 - x) * QS), cy = ex2((m1 - y) * QS);
    m0 = x; m1 = y;
#pragma unroll
    for (int j = 0; j < 3; j++) { o[4 * j] *= cx; o[4 * j + 1] *= cx; o[4 * j + 2] *= cy; o[4 * j + 3] *= cy; }
    const uint32_t p[4] = {pack2(ex2((s[0] - x) * QS), ex2((s[1] - x) * QS)), pack2(ex2((s[2] - y) * QS), ex2((s[3] - y) * QS)),
                           pack2(ex2((s[4] - x) * QS), ex2((s[5] - x) * QS)), pack2(ex2((s[6] - y) * QS), ex2((s[7] - y) * QS))};
    mma16816(o, p, trans8(v.x), trans8(v.y)); mma16816(o + 4, p, trans8(v.z), trans8(v.w)); mma16816(o + 8, p, 0x3F803F80u, 0x3F803F80u);
  }
}

__device__ __forceinline__ void store_o(const float (&o)[12], float g0, float g1, uint8_t* dst) {
  const float a = __fdividef(g0, o[8]), b = __fdividef(g1, o[10]);
  stg32(dst, pack2(o[0] * a, o[1] * a));
  stg32(dst + 128, pack2(o[2] * b, o[3] * b));
  stg32(dst + 1024, pack2(o[4] * a, o[5] * a));
  stg32(dst + 1152, pack2(o[6] * b, o[7] * b));
}

__device__ __forceinline__ void attn_passes(uint32_t (&qh)[4][4], uint32_t (&qb)[4][4], float qn, float g0, float g1, uint8_t* odst, uint32_t* oflag, int wg) {
  const int lane = threadIdx.x & 31;
#pragma unroll 1
  for (int p = 0; p < 2; p++) {
    {
      float o0[12], o1[12];
      attn_fast(qh[0], qh[1], o0, o1, lane);
      store_o(o0, g0, g1, odst);
      store_o(o1, g0, g1, odst + 2048);
      const float kn = __uint_as_float(lds32(sb + MISC_OFF + 32));
      const float lo = fminf(fminf(o0[8], o0[10]), fminf(o1[8], o1[10])), hi = (o0[8] + o0[10]) + (o1[8] + o1[10]);
      const bool ok = !FORCE_SLOW && qn * kn <= 372.f && qn <= 65536.f && kn <= 65536.f && lo >= 128.f && hi < INFINITY;
      if (!__all_sync(~0u, ok)) {
#pragma unroll 1
        for (int h = 0; h < 2; h++) {
          float o[12];
          attn_online(qb[0], o, lane);
          store_o(o, g0, g1, odst + h * 2048);
#pragma unroll
          for (int i = 0; i < 4; i++) qb[0][i] = qb[1][i];
        }
      }
    }
    if (p == 0) {
      __syncwarp();
      if (lane == 0) mbar_arrive(sb + B_PUB + 32);
    } else {
      bar_sync(1 + wg);
      if ((threadIdx.x & 127) == 0) { fence_gpu(); st_rlx(oflag, 1); }
    }
    odst += 32 * 1024;
#pragma unroll
    for (int i = 0; i < 4; i++) { qh[0][i] = qh[2][i]; qh[1][i] = qh[3][i]; qb[0][i] = qb[2][i]; qb[1][i] = qb[3][i]; }
  }
}

__device__ __forceinline__ float geglu(float x, float u, float c) {
  const float y = x * fmaf(x * x, 0.044715f * 0.7978845608028654f, 0.7978845608028654f);
  float t; asm("tanh.approx.f32 %0, %1;" : "=f"(t) : "f"(y));
  const float h = x * u * c;
  return fmaf(h, t, h);
}
__device__ __forceinline__ void store_h(const float (&d)[64], float c0, float c1, uint8_t* dst) {
#pragma unroll
  for (int j = 0; j < 8; j++) {
    stg32(dst + j * 1024, pack2(geglu(d[4 * j], d[32 + 4 * j], c0), geglu(d[4 * j + 1], d[33 + 4 * j], c0)));
    stg32(dst + j * 1024 + 128, pack2(geglu(d[4 * j + 2], d[34 + 4 * j], c1), geglu(d[4 * j + 3], d[35 + 4 * j], c1)));
  }
}

__global__ void __launch_bounds__(512, 1)
fused_kernel(const __grid_constant__ Maps mp, const __nv_bfloat16* __restrict__ gate_w, const uint8_t* __restrict__ wd_raw, const uint8_t* __restrict__ wo_raw) {
  extern __shared__ __align__(1024) uint8_t smem[];
  const int tid = threadIdx.x, lane = tid & 31;
  const int warp = __shfl_sync(~0u, tid >> 5, 0);
  const int wg = warp >> 2, wq4 = warp & 3;
  const int tb = blockIdx.x >> 3, cg = blockIdx.x & 7;
  const int half = cg & 1;

  if (warp == 12) {
    if (lane == 0) {
      EV(0);
      if ((uint32_t)__cvta_generic_to_shared(smem) != sb) __trap();
      for (int i = 0; i < 8; i++) mbar_init(sb + B_XFULL + 8 * i, 1);
      mbar_init(sb + B_WKV, 1);
      for (int i = 0; i < 4; i++) mbar_init(sb + B_WQ + 8 * i, i == 3 ? 2 : 1);
      asm volatile("fence.mbarrier_init.release.cluster;" ::: "memory");
    }
    __syncwarp();
    if (cg < 4) { const CUtensorMap* m = cg < 2 ? &mp.wk : &mp.wv; u_tma2d_pair(sb + B_WKV, sb + KV_OFF, m, m, 0, 0, 256); }
#pragma unroll
    for (int hh = 0; hh < 2; hh++) {
      const int h = hh ^ half;
#pragma unroll
      for (int j = 0; j < 4; j++) u_tma3d(sb + B_XFULL + 32 * h + 8 * j, 16384, sb + X_OFF + h * 65536 + j * 16384, &mp.x, 0, tb * 128 + h * 64, 2 * j);
#pragma unroll
      for (int s = 2 * hh; s < 2 * hh + 2; s++) u_tma3d(sb + B_WQ + 8 * s, 16384, sb + W_OFF + s * 16384, &mp.wq, cg * 32, s * 128, 0);
    }
    u_bulk(sb + B_WQ + 24, 1024, sb + GW_OFF, gate_w);
  } else if (tid == 416) {
    mbar_init(sb + B_GREADY, 8); mbar_init(sb + B_FFN1, 4);
    for (int i = 0; i < 4; i++) { mbar_init(sb + B_WFULL + 8 * i, 1); mbar_init(sb + B_WEMPTY + 8 * i, 8); mbar_init(sb + B_KVFULL + 8 * i, 1); mbar_init(sb + B_KVEMPTY + 8 * i, 8); mbar_init(sb + B_PUB + 8 * i, 4); }
    mbar_init(sb + B_PUB + 32, 8);
    for (int i = 0; i < 8; i++) { mbar_init(sb + B_FFULL + 8 * i, 2); mbar_init(sb + B_FEMPTY + 8 * i, 4); }
    asm volatile("fence.mbarrier_init.release.cluster;" ::: "memory");
  } else if (tid == 448) {
    asm volatile("prefetch.tensormap [%0];" ::"l"(&mp.wg) : "memory");
    asm volatile("prefetch.tensormap [%0];" ::"l"(&mp.wu) : "memory");
    asm volatile("prefetch.tensormap [%0];" ::"l"(&mp.wd) : "memory");
    asm volatile("prefetch.tensormap [%0];" ::"l"(&mp.wo) : "memory");
    asm volatile("prefetch.tensormap [%0];" ::"l"(&mp.out) : "memory");
  }
  if (tid < 128) { sts32(sb + ONES_OFF + tid * 4, 0x3C003C00u); asm volatile("fence.proxy.async.shared::cta;" ::: "memory"); }
  __syncthreads();
  if (tid == 0) EV(1);

  uint8_t* const a_tb = g_a + (size_t)(tb * 2) * A_BYTES;
  uint32_t* const fl_tb = g_flags + 64 + tb * 128;

  if (wg == 3) {
    asm volatile("setmaxnreg.dec.sync.aligned.u32 %0;" ::"n"(REG_PROD));
    if (wq4 == 0) {
#pragma unroll 1
      for (int n = 0; n < 32; n++) {
        const int s = n & 3;
        const int hc = n < 24 ? (n & 24) + cg : 24 + (cg >> 1);
        mbar_wait_sleep<NS_W>(sb + B_WEMPTY + 8 * s, (n >> 2) & 1);
        u_tma2d_pair(sb + B_WFULL + 8 * s, sb + W_OFF + s * 16384, &mp.wg, &mp.wu, hc * 64, (n & 7) * 64, (n & 7) * 64);
        if (n == 8) { u_prefetch(wd_raw + blockIdx.x * 14336, 14336); u_prefetch(wo_raw + blockIdx.x * 4096, 4096); }
      }
      mbar_wait_sleep<NS_W>(sb + B_FFN1, 0);
#pragma unroll 1
      for (int n = 0; n < 36; n++) {
        const int s = n & 7;
        mbar_wait_sleep<NS_W>(sb + B_FEMPTY + 8 * s, ((n >> 3) & 1) ^ 1);
        u_tma3d(sb + B_FFULL + 8 * s, 16384, sb + s * FST + 8192, n < 28 ? &mp.wd : &mp.wo, 0, (n < 28 ? n : n - 28) * 64, cg & 6);
      }
    } else if (wq4 == 1) {
      uint64_t f;
      for (int i = 0;; i++) {
        f = ld_acq64(g_flags + 2 * lane);
        if (__all_sync(~0u, (uint32_t)f != 0 && (f >> 32) != 0)) break;
        if (i > 0x100000) __trap();
      }
      const uint32_t fk = __reduce_max_sync(~0u, max((uint32_t)f, (uint32_t)(f >> 32)));
      if (lane == 0) { EV(4); sts32(sb + MISC_OFF + 32, fk); }
      fence_async_gl();
      __syncwarp();
#pragma unroll 1
      for (int n = 0; n < 33; n++) {
        const int s = n & 3;
        mbar_wait_sleep<NS_KV>(sb + B_KVEMPTY + 8 * s, ((n >> 2) & 1) ^ 1);
        u_bulk(sb + B_KVFULL + 8 * s, 8192, sb + KV_OFF + s * 8192, g_kv + (n & 15) * 8192);
      }
    } else if (wq4 == 3) {
      if (cg < 4) {
        asm volatile("bar.sync 4, 160;" ::: "memory");
        const uint32_t m = max(max(lds32(sb + MISC_OFF + 48), lds32(sb + MISC_OFF + 52)), max(lds32(sb + MISC_OFF + 56), lds32(sb + MISC_OFF + 60)));
        fence_gpu();
        if (lane == 0) { st_rlx(g_flags + (tb * 2 + half) * 2 + (cg >> 1), m | 1); EV(2); }
      }
#pragma unroll 1
      for (int e = 0; e < 5; e++) {
        mbar_wait_sleep<NS_W>(sb + B_PUB + 8 * e, 0);
        fence_gpu();
        const int idx = e < 3 ? 2 * (e * 8 + cg) : e == 3 ? 2 * (24 + (cg >> 1)) : 2 * cg + 1;
        if (lane < 2 && (e != 3 || lane == half)) st_rlx(fl_tb + lane * 64 + idx, 1);
      }
    } else {
      mbar_wait_sleep<NS_W>(sb + B_FFN1, 0);
      const uint32_t* fl = fl_tb + half * 64 + 2 * lane;
      const uint8_t* src = a_tb + half * A_BYTES;
      int ready = 0;
#pragma unroll 1
      for (int n = 0; n < 36; n++) {
        if (n >= ready) {
          for (int i = 0;; i++) {
            const uint64_t f = ld_acq64(fl);
            const uint32_t rh = __ballot_sync(~0u, (uint32_t)f != 0), ro = __ballot_sync(~0u, (f >> 32) != 0);
            ready = __ffs(~rh) - 1;
            if (ready == 28) ready += (__ffs(~ro) - 1) >> 1;
            if (n < ready) break;
            if (i > 0x100000) __trap();
            __nanosleep(NS_F);
          }
          fence_async_gl();
        }
        const int s = n & 7;
        mbar_wait_sleep<NS_W>(sb + B_FEMPTY + 8 * s, ((n >> 3) & 1) ^ 1);
        u_bulk(sb + B_FFULL + 8 * s, 8192, sb + s * FST, src + n * 8192);
      }
      uint32_t last = 0;
      if (lane == 0) { __threadfence(); last = atomicAdd(&g_done, 1) == gridDim.x - 1; __threadfence(); }
      if (__shfl_sync(~0u, last, 0)) {
        for (int i = lane; i < (64 + 32 * 64) / 4; i += 32) reinterpret_cast<uint4*>(g_flags)[i] = make_uint4(0, 0, 0, 0);
        if (lane == 0) g_done = 0;
      }
    }
  } else if (wg == 2) {
    asm volatile("setmaxnreg.inc.sync.aligned.u32 %0;" ::"n"(REG_GEMM));
    float d0[64], d1[64];
    zero(d0); zero(d1);
    const uint32_t xl = dlo(sb + X_OFF, 16), wl = dlo(sb + W_OFF, 8192);
    constexpr uint32_t H128 = dhi(1024, 1);
    uint8_t* const hdst = a_tb + wq4 * 256 + lane * 4;
    const uint32_t grow = sb + G_OFF + (wq4 * 16 + (lane >> 2)) * 4;
#pragma unroll 1
    for (int st = 0; st < 3; st++) {
#pragma unroll 1
      for (int kc = 0; kc < 8; kc++) {
        const int s = kc & 3;
        if (st == 0) { mbar_wait(sb + B_XFULL + 8 * (kc >> 1), 0); mbar_wait(sb + B_XFULL + 32 + 8 * (kc >> 1), 0); }
        mbar_wait(sb + B_WFULL + 8 * s, (kc >> 2) & 1);
        const uint32_t a = xl + kc * 512, b = wl + s * 1024;
#pragma unroll
        for (int k = 0; k < 4; k++) {
          wg_fence();
          mma_ss_t128(d0, mk64(a + 2 * k, H128), mk64(b + 128 * k, H128), (kc | k) != 0);
          mma_ss_t128(d1, mk64(a + 4096 + 2 * k, H128), mk64(b + 128 * k, H128), (kc | k) != 0);
          wg_commit(); wg_wait<GW1>();
          if (GW1 && k == 0 && kc != 0 && lane == 0) mbar_arrive2(sb + B_WEMPTY + 8 * ((s + 3) & 3));
        }
        if (!GW1 && lane == 0) mbar_arrive2(sb + B_WEMPTY + 8 * s);
      }
      if (GW1) { wg_wait<0>(); if (lane == 0) mbar_arrive2(sb + B_WEMPTY + 8 * 3); }
      pin(d0); pin(d1);
      if (st == 0) { if (tid == 256) EV(8); mbar_wait(sb + B_GREADY, 0); }
      const int hc = st * 8 + cg;
      store_h(d0, __uint_as_float(lds32(grow)), __uint_as_float(lds32(grow + 32)), hdst + hc * 8192);
      store_h(d1, __uint_as_float(lds32(grow + 256)), __uint_as_float(lds32(grow + 288)), hdst + A_BYTES + hc * 8192);
      __syncwarp();
      if (lane == 0) mbar_arrive(sb + B_PUB + 8 * st);
      pin(d0); pin(d1);
    }
    {
#pragma unroll 1
      for (int kc = 0; kc < 8; kc++) {
        const int s = kc & 3;
        mbar_wait(sb + B_WFULL + 8 * s, (kc >> 2) & 1);
        const uint32_t a = xl + kc * 512 + half * 4096, b = wl + s * 1024;
#pragma unroll
        for (int k = 0; k < 4; k += 2) {
          wg_fence();
          mma_ss_t128(d0, mk64(a + 2 * k, H128), mk64(b + 128 * k, H128), (kc | k) != 0);
          mma_ss_t128(d0, mk64(a + 2 * k + 2, H128), mk64(b + 128 * k + 128, H128), 1);
          wg_commit(); wg_wait<GW1>();
          if (GW1 && k == 0 && kc != 0 && lane == 0) mbar_arrive2(sb + B_WEMPTY + 8 * ((s + 3) & 3));
        }
        if (!GW1 && lane == 0) mbar_arrive2(sb + B_WEMPTY + 8 * s);
      }
      wg_wait<0>();
      pin(d0);
      if (lane == 0) mbar_arrive(sb + B_FFN1);
      if (tid == 256) EV(12);
      const int hc = 24 + (cg >> 1);
      store_h(d0, __uint_as_float(lds32(grow + half * 256)), __uint_as_float(lds32(grow + half * 256 + 32)), hdst + half * A_BYTES + hc * 8192);
      __syncwarp();
      if (lane == 0) mbar_arrive(sb + B_PUB + 24);
      pin(d0);
    }
    const uint32_t al = dlo(sb, 1024), bl = dlo(sb + 8192, 8192);
    constexpr uint32_t HA = dhi(128, 0);
#pragma unroll 1
    for (int n = 0; n < 36; n++) {
      const int s = n & 7;
      mbar_wait_sleep<NS_G>(sb + B_FFULL + 8 * s, (n >> 3) & 1);
      const uint32_t a = al + s * (FST >> 4), b = bl + s * (FST >> 4);
#pragma unroll
      for (int k = 0; k < 4; k += 2) {
        wg_fence();
        mma_ss_t128(d0, mk64(a + 128 * k, HA), mk64(b + 128 * k, H128), (n | k) != 0);
        mma_ss_t128(d0, mk64(a + 128 * k + 128, HA), mk64(b + 128 * k + 128, H128), 1);
        wg_commit(); wg_wait<GW2>();
        if (GW2 && k == 0 && n != 0 && lane == 0) mbar_arrive(sb + B_FEMPTY + 8 * ((s + 7) & 7));
      }
      if (!GW2 && lane == 0) mbar_arrive(sb + B_FEMPTY + 8 * s);
    }
    wg_wait<0>();
    pin(d0);
    if (tid == 256) EV(19);
    const uint32_t stg = sb + 4 * FST;
    const int r = wq4 * 16 + (lane & 7) + ((lane >> 3) & 1) * 8;
#pragma unroll
    for (int j = 0; j < 8; j++) {
      const int c16 = (2 * j + (lane >> 4)) & 7;
      const uint32_t ad = stg + (j >> 2) * 8192 + r * 128 + ((c16 ^ (r & 7)) << 4);
      asm volatile("stmatrix.sync.aligned.m8n8.x4.shared.b16 [%0], {%1,%2,%3,%4};" ::"r"(ad), "r"(pack2(d0[8 * j], d0[8 * j + 1])), "r"(pack2(d0[8 * j + 2], d0[8 * j + 3])),
                   "r"(pack2(d0[8 * j + 4], d0[8 * j + 5])), "r"(pack2(d0[8 * j + 6], d0[8 * j + 7])) : "memory");
    }
    asm volatile("fence.proxy.async.shared::cta;" ::: "memory");
    bar_sync(3);
    if (tid == 256) {
      asm volatile("cp.async.bulk.tensor.3d.global.shared::cta.bulk_group [%0, {%2, %3, %4}], [%1];" ::"l"(&mp.out), "r"(stg), "r"(0), "r"(tb * 128 + half * 64), "r"(cg & 6) : "memory");
      asm volatile("cp.async.bulk.commit_group;" ::: "memory");
      asm volatile("cp.async.bulk.wait_group.read 0;" ::: "memory");
      EV(20);
    }
  } else {
    asm volatile("setmaxnreg.inc.sync.aligned.u32 %0;" ::"n"(REG_ATT));
    constexpr uint32_t H128 = dhi(1024, 1);
    const uint32_t xl = dlo(sb + X_OFF + wg * 65536, 16);
    if (cg < 4 && wg == half) {
      float d[8];
      zero(d);
      mbar_wait(sb + B_WKV, 0);
      const uint32_t wl = dlo(sb + KV_OFF, 16);
#pragma unroll 1
      for (int j = 0; j < 4; j++) {
        mbar_wait(sb + B_XFULL + 32 * wg + 8 * j, 0);
        wg_fence();
#pragma unroll
        for (int k = 0; k < 8; k++) mma_ss_t16(d, mk64(xl + j * 1024 + (k >> 2) * 512 + 2 * (k & 3), H128), KD(wl + j * 256 + 32 * k), 1);
        wg_commit();
      }
      wg_wait<0>(); pin(d);
      const float sc = cg < 2 ? 0.0625f : 1.f;
      const int r = lane >> 2;
      uint8_t* dst = g_kv + (tb * 2 + wg) * 4096 + (cg >> 1) * 2048 + (wq4 * 16 + r) * 32 + (lane & 3) * 4;
      const int sw = (r >> 2) * 16;
      stg32(dst + sw, packh(d[0] * sc, d[1] * sc)); stg32(dst + 256 + sw, packh(d[2] * sc, d[3] * sc));
      stg32(dst + (sw ^ 16), packh(d[4] * sc, d[5] * sc)); stg32(dst + 256 + (sw ^ 16), packh(d[6] * sc, d[7] * sc));
      g_kvb[(tb * 8 + warp) * 64 + (cg >> 1) * 32 + lane] = make_uint4(pack2(d[0], d[1]), pack2(d[2], d[3]), pack2(d[4], d[5]), pack2(d[6], d[7]));
      uint32_t mx;
      if (cg < 2) {
        float n0 = sq4(d[0], d[1], d[4], d[5]), n1 = sq4(d[2], d[3], d[6], d[7]);
        n0 += __shfl_xor_sync(~0u, n0, 1); n1 += __shfl_xor_sync(~0u, n1, 1);
        n0 += __shfl_xor_sync(~0u, n0, 2); n1 += __shfl_xor_sync(~0u, n1, 2);
        mx = __reduce_max_sync(~0u, max(__float_as_uint(n0), __float_as_uint(n1)));
      } else {
        bool ok = true;
#pragma unroll
        for (int i = 0; i < 4; i++) {
          const int j = (i & 1) + (i >> 1) * 4;
          uint32_t c = max(__float_as_uint(d[j]) & 0x7fffffffu, __float_as_uint(d[j + 2]) & 0x7fffffffu);
          c = max(c, __shfl_xor_sync(~0u, c, 4)); c = max(c, __shfl_xor_sync(~0u, c, 8)); c = max(c, __shfl_xor_sync(~0u, c, 16));
          ok = ok && (c == 0 || (c >= 0x37800000u && c <= 0x47000000u));
        }
        mx = __all_sync(~0u, ok) ? 0 : 0x7f800001u;
      }
      if (lane == 0) sts32(sb + MISC_OFF + 48 + wq4 * 4, mx);
      asm volatile("bar.arrive 4, 160;" ::: "memory");
    }
    uint32_t qh[4][4], qb[4][4];
    float g0, g1, qn;
    {
      float d[32], e[4];
      zero(d); zero(e);
      const uint32_t wl = dlo(sb + W_OFF, 8192), gl = dlo(sb + GW_OFF, 16);
#pragma unroll 1
      for (int s = 0; s < 4; s++) {
        mbar_wait(sb + B_XFULL + 32 * wg + 8 * s, 0);
        mbar_wait(sb + B_WQ + 8 * s, 0);
        wg_fence();
#pragma unroll
        for (int k = 0; k < 8; k++) mma_ss_t64(d, mk64(xl + (2 * s + (k >> 2)) * 512 + 2 * (k & 3), H128), mk64(wl + s * 1024 + 64 * k, dhi(512, 2)), 1);
        wg_commit(); wg_wait<0>();
        if (lane == 0) mbar_arrive(sb + B_WEMPTY + 8 * s);
      }
      pin(d);
      wg_fence();
#pragma unroll
      for (int k = 0; k < 32; k++) mma_ss_n8(e, mk64(xl + (k >> 2) * 512 + 2 * (k & 3), H128), mk64(gl + 2 * k, dhi(128, 0)), 1);
      wg_commit();
      uint32_t nm = 0;
#pragma unroll
      for (int h = 0; h < 4; h++) {
        const float* dh = d + 8 * h;
#pragma unroll
        for (int i = 0; i < 4; i++) {
          const float c = (i & 1) ? QS / 32.f : QS * 16.f;
          qh[h][i] = packh(dh[2 * i] * c, dh[2 * i + 1] * c);
          qb[h][i] = pack2(dh[2 * i], dh[2 * i + 1]);
        }
        float n0 = sq4(dh[0], dh[1], dh[4], dh[5]), n1 = sq4(dh[2], dh[3], dh[6], dh[7]);
        n0 += __shfl_xor_sync(~0u, n0, 1); n1 += __shfl_xor_sync(~0u, n1, 1);
        n0 += __shfl_xor_sync(~0u, n0, 2); n1 += __shfl_xor_sync(~0u, n1, 2);
        nm = max(nm, max(__float_as_uint(n0), __float_as_uint(n1)));
      }
      qn = __uint_as_float(nm) * (QS * QS);
      wg_wait<0>(); pin(e);
      const float z0 = __shfl_sync(~0u, e[0], lane & ~3), z1 = __shfl_sync(~0u, e[2], lane & ~3);
      g0 = 1.f / (1.f + __expf(-z0)); g1 = 1.f / (1.f + __expf(-z1));
      if ((lane & 3) == 0) {
        const uint32_t ga = sb + G_OFF + (wg * 64 + wq4 * 16 + (lane >> 2)) * 4;
        sts32(ga, __float_as_uint(0.5f * (1.f - g0))); sts32(ga + 32, __float_as_uint(0.5f * (1.f - g1)));
      }
      __syncwarp();
      if (lane == 0) mbar_arrive(sb + B_GREADY);
    }
    if (tid == 0) EV(3);
    mbar_wait(sb + B_KVFULL, 0);
    if (tid == 0) { EV(5); EVC(0); }
    uint8_t* odst = a_tb + wg * A_BYTES + (224 + cg * 4) * 1024 + wq4 * 256 + lane * 4;
    uint32_t* const oflag = fl_tb + wg * 64 + 2 * (8 + cg) + 1;
    attn_passes(qh, qb, qn, g0, g1, odst, oflag, wg);
  }
}

typedef CUresult (*EncodeFn)(CUtensorMap*, CUtensorMapDataType, cuuint32_t, void*, const cuuint64_t*, const cuuint64_t*, const cuuint32_t*, const cuuint32_t*,
                             CUtensorMapInterleave, CUtensorMapSwizzle, CUtensorMapL2promotion, CUtensorMapFloatOOBfill);

void make_map(EncodeFn fn, CUtensorMap* m, const void* p, uint64_t cols, uint64_t rows, uint32_t bc, uint32_t br, CUtensorMapSwizzle sw) {
  cuuint64_t dims[2] = {cols, rows}, strides[1] = {cols * 2};
  cuuint32_t box[2] = {bc, br}, es[2] = {1, 1};
  fn(m, CU_TENSOR_MAP_DATA_TYPE_BFLOAT16, 2, const_cast<void*>(p), dims, strides, box, es, CU_TENSOR_MAP_INTERLEAVE_NONE, sw,
     CU_TENSOR_MAP_L2_PROMOTION_L2_128B, CU_TENSOR_MAP_FLOAT_OOB_FILL_NONE);
}

void make_map3(EncodeFn fn, CUtensorMap* m, const void* p, uint64_t bw, uint64_t nblk, uint64_t rows, uint32_t bc, uint32_t br, CUtensorMapSwizzle sw) {
  cuuint64_t dims[3] = {bw, rows, nblk}, strides[2] = {bw * nblk * 2, bw * 2};
  cuuint32_t box[3] = {bc, br, 2}, es[3] = {1, 1, 1};
  fn(m, CU_TENSOR_MAP_DATA_TYPE_BFLOAT16, 3, const_cast<void*>(p), dims, strides, box, es, CU_TENSOR_MAP_INTERLEAVE_NONE, sw,
     CU_TENSOR_MAP_L2_PROMOTION_L2_128B, CU_TENSOR_MAP_FLOAT_OOB_FILL_NONE);
}

}

extern "C" void kernel_launch(void* const* d_in, const int* in_sizes, int n_in, void* d_out, int out_size) {
  void* fp = nullptr;
  cudaDriverEntryPointQueryResult qr;
  cudaGetDriverEntryPoint("cuTensorMapEncodeTiled", &fp, cudaEnableDefault, &qr);
  EncodeFn fn = (EncodeFn)fp;
  Maps mp;
  make_map3(fn, &mp.x, d_in[0], 64, 8, S_, 64, 64, CU_TENSOR_MAP_SWIZZLE_128B);
  make_map3(fn, &mp.wq, d_in[1], 256, 2, D_, 32, 128, CU_TENSOR_MAP_SWIZZLE_64B);
  make_map(fn, &mp.wk, d_in[2], 16, D_, 16, 256, CU_TENSOR_MAP_SWIZZLE_32B);
  make_map(fn, &mp.wv, d_in[3], 16, D_, 16, 256, CU_TENSOR_MAP_SWIZZLE_32B);
  make_map3(fn, &mp.wo, d_in[4], 64, 8, D_, 64, 64, CU_TENSOR_MAP_SWIZZLE_128B);
  make_map(fn, &mp.wg, d_in[6], F_, D_, 64, 64, CU_TENSOR_MAP_SWIZZLE_128B);
  make_map(fn, &mp.wu, d_in[7], F_, D_, 64, 64, CU_TENSOR_MAP_SWIZZLE_128B);
  make_map3(fn, &mp.wd, d_in[8], 64, 8, F_, 64, 64, CU_TENSOR_MAP_SWIZZLE_128B);
  make_map3(fn, &mp.out, d_out, 64, 8, S_, 64, 64, CU_TENSOR_MAP_SWIZZLE_128B);
  cudaFuncSetAttribute(fused_kernel, cudaFuncAttributeMaxDynamicSharedMemorySize, SMEM_BYTES);
  fused_kernel<<<128, 512, SMEM_BYTES, cudaStreamPerThread>>>(mp, (const __nv_bfloat16*)d_in[9], (const uint8_t*)d_in[8], (const uint8_t*)d_in[4]);
}
```

```cpp
#include <cuda_runtime.h>
#include <cuda_bf16.h>
#include <cuda.h>
#include <stdint.h>

#define DEG 2
#define REG_ATT 160
#define REG_GEMM 160
#define REG_PROD 32
#define FORCE_SLOW 0
#define NS_W 100
#define NS_KV 200
#define NS_F 200
#define NS_G 50
#define GW1 0
#define GW2 1
#define HINT 4000
#define EXP 0

namespace {

constexpr int S_ = 2048, D_ = 512, F_ = 1792;
constexpr float QS = 0.25f * 1.4426950408889634f;

constexpr uint32_t sb = 1024;
constexpr uint32_t X_OFF = 0;
constexpr uint32_t W_OFF = 131072;
constexpr uint32_t KV_OFF = 196608;
constexpr uint32_t ONES_OFF = 229376;
constexpr uint32_t G_OFF = 229888;
constexpr uint32_t MISC_OFF = 231552;
constexpr uint32_t BAR_OFF = 231616;
constexpr uint32_t B_XFULL = BAR_OFF;
constexpr uint32_t B_PUB = B_XFULL + 64;
constexpr uint32_t B_GREADY = B_XFULL + 128;
constexpr uint32_t B_FFN1 = B_GREADY + 8;
constexpr uint32_t B_WFULL = B_FFN1 + 8;
constexpr uint32_t B_WEMPTY = B_WFULL + 32;
constexpr uint32_t B_KVFULL = B_WEMPTY + 32;
constexpr uint32_t B_KVEMPTY = B_KVFULL + 32;
constexpr uint32_t B_FFULL = B_KVEMPTY + 32;
constexpr uint32_t B_FEMPTY = B_FFULL + 64;
constexpr uint32_t B_WQ = B_FEMPTY + 64;
constexpr uint32_t SMEM_BYTES = B_WQ + 32;
constexpr uint32_t FST = 24576;
static_assert(SMEM_BYTES <= 232448, "smem");

constexpr int A_BYTES = 288 * 1024;
__device__ __align__(1024) uint8_t g_kv[32 * 4096];
__device__ uint4 g_kvb[128 * 64];
__device__ __align__(1024) float2 g_gate[S_];
__device__ __align__(1024) uint8_t g_a[32 * A_BYTES];
__device__ __align__(256) uint32_t g_flags[64 + 32 * 64];
__device__ uint32_t g_done;

#define EV(i)
#define EVC(i)
struct Maps { CUtensorMap x, wq, wo, wg, wu, wd, out; };

__device__ __forceinline__ void wg_fence() { asm volatile("wgmma.fence.sync.aligned;" ::: "memory"); }
__device__ __forceinline__ void wg_commit() { asm volatile("wgmma.commit_group.sync.aligned;" ::: "memory"); }
template <int N> __device__ __forceinline__ void wg_wait() { asm volatile("wgmma.wait_group.sync.aligned %0;" ::"n"(N) : "memory"); }
template <int N> __device__ __forceinline__ void pin(float (&d)[N]) {
#pragma unroll
  for (int i = 0; i < N; i++) asm volatile("" : "+f"(d[i])::"memory");
}
template <int N> __device__ __forceinline__ void pinu(uint32_t (&d)[N]) {
#pragma unroll
  for (int i = 0; i < N; i++) asm volatile("" : "+r"(d[i])::"memory");
}
template <int N> __device__ __forceinline__ void zero(float (&d)[N]) {
#pragma unroll
  for (int i = 0; i < N; i++) d[i] = 0.f;
  pin(d);
}
__device__ __forceinline__ uint64_t mk64(uint32_t lo, uint32_t hi) { return ((uint64_t)hi << 32) | lo; }
__host__ __device__ constexpr uint32_t dhi(uint32_t sbo, uint32_t sw) { return (sbo >> 4) | (sw << 30); }
__device__ __forceinline__ uint32_t dlo(uint32_t addr, uint32_t lbo) { return (addr >> 4) | ((lbo >> 4) << 16); }

__device__ __forceinline__ void mbar_init(uint32_t b, uint32_t n) { asm volatile("mbarrier.init.shared::cta.b64 [%0], %1;" ::"r"(b), "r"(n) : "memory"); }
__device__ __forceinline__ void mbar_arrive(uint32_t b) { asm volatile("mbarrier.arrive.shared::cta.b64 _, [%0];" ::"r"(b) : "memory"); }
__device__ __forceinline__ void mbar_arrive2(uint32_t b) { asm volatile("mbarrier.arrive.shared::cta.b64 _, [%0], 2;" ::"r"(b) : "memory"); }
__device__ __forceinline__ void mbar_expect(uint32_t b, uint32_t bytes) { asm volatile("mbarrier.arrive.expect_tx.shared::cta.b64 _, [%0], %1;" ::"r"(b), "r"(bytes) : "memory"); }
__device__ __forceinline__ void mbar_wait(uint32_t b, uint32_t parity) {
  asm volatile(
      "{\n.reg .pred p;\n.reg .u32 c;\n"
      "mbarrier.try_wait.parity.shared::cta.b64 p, [%0], %1;\n"
      "@p bra DONE;\n"
      "mov.u32 c, 0;\n"
      "SPIN:\n"
      "mbarrier.try_wait.parity.shared::cta.b64 p, [%0], %1;\n"
      "@p bra DONE;\n"
      "add.u32 c, c, 1;\n"
      "setp.lt.u32 p, c, 0x100000;\n"
      "@p bra SPIN;\n"
      "trap;\n"
      "DONE:\n}\n" ::"r"(b), "r"(parity) : "memory");
}
template <int NS> __device__ __forceinline__ void mbar_wait_sleep(uint32_t b, uint32_t parity) {
  asm volatile(
      "{\n.reg .pred p;\n.reg .u32 c;\n"
      "mov.u32 c, 0;\n"
      "SPIN:\n"
      "mbarrier.try_wait.parity.shared::cta.b64 p, [%0], %1, %2;\n"
      "@p bra.uni DONE;\n"
      "add.u32 c, c, 1;\n"
      "setp.lt.u32 p, c, 0x40000;\n"
      "@p bra.uni SPIN;\n"
      "trap;\n"
      "DONE:\n}\n" ::"r"(b), "r"(parity), "n"(HINT) : "memory");
  return;
  asm volatile(
      "{\n.reg .pred p;\n.reg .u32 c;\n"
      "mov.u32 c, 0;\n"
      "SPIN:\n"
      "mbarrier.test_wait.parity.shared::cta.b64 p, [%0], %1;\n"
      "@p bra.uni DONE;\n"
      "nanosleep.u32 %2;\n"
      "add.u32 c, c, 1;\n"
      "setp.lt.u32 p, c, 0x100000;\n"
      "@p bra.uni SPIN;\n"
      "trap;\n"
      "DONE:\n}\n" ::"r"(b), "r"(parity), "n"(NS) : "memory");
}
#define ELECT "{\n.reg .pred p;\nelect.sync _|p, 0xffffffff;\n@p mbarrier.arrive.expect_tx.shared::cta.b64 _, [%0], %1;\n"
__device__ __forceinline__ void u_tma3d(uint32_t bar, uint32_t bytes, uint32_t dst, const CUtensorMap* m, int c0, int c1, int c2) {
  asm volatile(ELECT "@p cp.async.bulk.tensor.3d.shared::cluster.global.mbarrier::complete_tx::bytes [%2], [%3, {%4, %5, %6}], [%0];\n}\n" ::"r"(bar), "r"(bytes), "r"(dst), "l"(m), "r"(c0), "r"(c1), "r"(c2) : "memory");
}
__device__ __forceinline__ void u_tma4d(uint32_t bar, uint32_t bytes, uint32_t dst, const CUtensorMap* m, int c1, int c2, int c3) {
  asm volatile(ELECT "@p cp.async.bulk.tensor.4d.shared::cluster.global.mbarrier::complete_tx::bytes [%2], [%3, {0, %4, %5, %6}], [%0];\n}\n" ::"r"(bar), "r"(bytes), "r"(dst), "l"(m), "r"(c1), "r"(c2), "r"(c3) : "memory");
}
__device__ __forceinline__ void u_tma2d(uint32_t bar, uint32_t bytes, uint32_t dst, const CUtensorMap* m, int c0, int c1) {
  asm volatile(ELECT "@p cp.async.bulk.tensor.2d.shared::cluster.global.mbarrier::complete_tx::bytes [%2], [%3, {%4, %5}], [%0];\n}\n" ::"r"(bar), "r"(bytes), "r"(dst), "l"(m), "r"(c0), "r"(c1) : "memory");
}
__device__ __forceinline__ void u_tma2d_pair(uint32_t bar, uint32_t dst, const CUtensorMap* m0, const CUtensorMap* m1, int c0, int c1, int c1b) {
  asm volatile(ELECT "@p cp.async.bulk.tensor.2d.shared::cluster.global.mbarrier::complete_tx::bytes [%2], [%3, {%5, %6}], [%0];\n"
               "@p cp.async.bulk.tensor.2d.shared::cluster.global.mbarrier::complete_tx::bytes [%2 + 8192], [%4, {%5, %7}], [%0];\n}\n" ::"r"(bar), "r"(16384), "r"(dst), "l"(m0), "l"(m1), "r"(c0), "r"(c1), "r"(c1b) : "memory");
}
__device__ __forceinline__ void u_bulk(uint32_t bar, uint32_t bytes, uint32_t dst, const void* src) {
  asm volatile(ELECT "@p cp.async.bulk.shared::cluster.global.mbarrier::complete_tx::bytes [%2], [%3], %1, [%0];\n}\n" ::"r"(bar), "r"(bytes), "r"(dst), "l"(src) : "memory");
}
__device__ __forceinline__ void u_prefetch(const void* src, uint32_t bytes) {
  asm volatile("{\n.reg .pred p;\nelect.sync _|p, 0xffffffff;\n@p cp.async.bulk.prefetch.L2.global [%0], %1;\n}\n" ::"l"(src), "r"(bytes) : "memory");
}
__device__ __forceinline__ void fence_gpu() { asm volatile("fence.acq_rel.gpu;" ::: "memory"); }
__device__ __forceinline__ void st_rlx(uint32_t* p, uint32_t v) { asm volatile("st.relaxed.gpu.global.u32 [%0], %1;" ::"l"(p), "r"(v) : "memory"); }
__device__ __forceinline__ uint64_t ld_acq64(const uint32_t* p) { uint64_t v; asm volatile("ld.acquire.gpu.global.u64 %0, [%1];" : "=l"(v) : "l"(p) : "memory"); return v; }
__device__ __forceinline__ void tma2d(uint32_t dst, const CUtensorMap* m, int c0, int c1, uint32_t bar) {
  asm volatile("cp.async.bulk.tensor.2d.shared::cluster.global.mbarrier::complete_tx::bytes [%0], [%1, {%3, %4}], [%2];" ::"r"(dst), "l"(m), "r"(bar), "r"(c0), "r"(c1) : "memory");
}
__device__ __forceinline__ void bulk_ld(uint32_t dst, const void* src, uint32_t bytes, uint32_t bar) {
  asm volatile("cp.async.bulk.shared::cluster.global.mbarrier::complete_tx::bytes [%0], [%1], %2, [%3];" ::"r"(dst), "l"(src), "r"(bytes), "r"(bar) : "memory");
}
__device__ __forceinline__ void l2_prefetch(const void* src, uint32_t bytes) {
  asm volatile("cp.async.bulk.prefetch.L2.global [%0], %1;" ::"l"(src), "r"(bytes) : "memory");
}
__device__ __forceinline__ uint32_t ld_acq(const uint32_t* p) { uint32_t v; asm volatile("ld.acquire.gpu.global.u32 %0, [%1];" : "=r"(v) : "l"(p) : "memory"); return v; }
__device__ __forceinline__ void st_rel(uint32_t* p, uint32_t v) { asm volatile("st.release.gpu.global.u32 [%0], %1;" ::"l"(p), "r"(v) : "memory"); }
__device__ __forceinline__ void fence_async_all() { asm volatile("fence.proxy.async;" ::: "memory"); }
__device__ __forceinline__ void fence_async_gl() { asm volatile("fence.proxy.async.global;" ::: "memory"); }
__device__ __forceinline__ void bar_sync(int id) { asm volatile("bar.sync %0, 128;" ::"r"(id) : "memory"); }
__device__ __forceinline__ uint32_t pack2(float lo, float hi) { uint32_t r; asm("cvt.rn.bf16x2.f32 %0, %1, %2;" : "=r"(r) : "f"(hi), "f"(lo)); return r; }
__device__ __forceinline__ float ex2(float a) { float r; asm("ex2.approx.ftz.f32 %0, %1;" : "=f"(r) : "f"(a)); return r; }
__device__ __forceinline__ float sq4(float a, float b, float c, float d) { return fmaf(a, a, b * b) + fmaf(c, c, d * d); }
__device__ __forceinline__ void stg32(void* p, uint32_t v) { asm volatile("st.global.u32 [%0], %1;" ::"l"(p), "r"(v) : "memory"); }
__device__ __forceinline__ void stg64(void* p, uint32_t a, uint32_t b) { asm volatile("st.global.v2.u32 [%0], {%1, %2};" ::"l"(p), "r"(a), "r"(b) : "memory"); }
__device__ __forceinline__ void sts128(uint32_t a, uint32_t x, uint32_t y, uint32_t z, uint32_t w) { asm volatile("st.shared.v4.u32 [%0], {%1, %2, %3, %4};" ::"r"(a), "r"(x), "r"(y), "r"(z), "r"(w) : "memory"); }
__device__ __forceinline__ void sts32(uint32_t a, uint32_t v) { asm volatile("st.shared.u32 [%0], %1;" ::"r"(a), "r"(v) : "memory"); }
__device__ __forceinline__ uint32_t lds32(uint32_t a) { uint32_t v; asm volatile("ld.shared.u32 %0, [%1];" : "=r"(v) : "r"(a) : "memory"); return v; }

__device__ __forceinline__ void mma_qk(uint32_t (&d)[16], const uint32_t (&a)[4], uint64_t b) {
  asm volatile("{\n.reg .pred p;\nsetp.ne.b32 p, 0, 0;\n"
    "wgmma.mma_async.sync.aligned.m64n64k16.f16.f16.f16 {%0,%1,%2,%3,%4,%5,%6,%7,%8,%9,%10,%11,%12,%13,%14,%15}, {%16,%17,%18,%19}, %20, p, 1, 1, 0;\n}\n"
    : "+r"(d[0]),"+r"(d[1]),"+r"(d[2]),"+r"(d[3]),"+r"(d[4]),"+r"(d[5]),"+r"(d[6]),"+r"(d[7]),"+r"(d[8]),"+r"(d[9]),"+r"(d[10]),"+r"(d[11]),"+r"(d[12]),"+r"(d[13]),"+r"(d[14]),"+r"(d[15]) : "r"(a[0]),"r"(a[1]),"r"(a[2]),"r"(a[3]),"l"(b));
}
__device__ __forceinline__ void mma_pv(uint32_t (&d)[6], const uint32_t (&a)[4], uint64_t b) {
  asm volatile("{\n.reg .pred p;\nsetp.ne.b32 p, 1, 0;\n"
    "wgmma.mma_async.sync.aligned.m64n24k16.f16.f16.f16 {%0,%1,%2,%3,%4,%5}, {%6,%7,%8,%9}, %10, p, 1, 1, 1;\n}\n"
    : "+r"(d[0]),"+r"(d[1]),"+r"(d[2]),"+r"(d[3]),"+r"(d[4]),"+r"(d[5]) : "r"(a[0]),"r"(a[1]),"r"(a[2]),"r"(a[3]),"l"(b));
}
__device__ __forceinline__ void mma_pv0(uint32_t (&d)[6], const uint32_t (&a)[4], uint64_t b) {
  asm volatile("{\n.reg .pred p;\nsetp.ne.b32 p, 0, 0;\n"
    "wgmma.mma_async.sync.aligned.m64n24k16.f16.f16.f16 {%0,%1,%2,%3,%4,%5}, {%6,%7,%8,%9}, %10, p, 1, 1, 1;\n}\n"
    : "+r"(d[0]),"+r"(d[1]),"+r"(d[2]),"+r"(d[3]),"+r"(d[4]),"+r"(d[5]) : "r"(a[0]),"r"(a[1]),"r"(a[2]),"r"(a[3]),"l"(b));
}
__device__ __forceinline__ void mma_ss_t128(float (&d)[64], uint64_t a, uint64_t b, int acc) {
  asm volatile("{\n.reg .pred p;\nsetp.ne.b32 p, %66, 0;\n"
    "wgmma.mma_async.sync.aligned.m64n128k16.f32.bf16.bf16 {%0,%1,%2,%3,%4,%5,%6,%7,%8,%9,%10,%11,%12,%13,%14,%15,%16,%17,%18,%19,%20,%21,%22,%23,%24,%25,%26,%27,%28,%29,%30,%31,%32,%33,%34,%35,%36,%37,%38,%39,%40,%41,%42,%43,%44,%45,%46,%47,%48,%49,%50,%51,%52,%53,%54,%55,%56,%57,%58,%59,%60,%61,%62,%63}, %64, %65, p, 1, 1, 0, 1;\n}\n"
    : "+f"(d[0]),"+f"(d[1]),"+f"(d[2]),"+f"(d[3]),"+f"(d[4]),"+f"(d[5]),"+f"(d[6]),"+f"(d[7]),"+f"(d[8]),"+f"(d[9]),"+f"(d[10]),"+f"(d[11]),"+f"(d[12]),"+f"(d[13]),"+f"(d[14]),"+f"(d[15]),"+f"(d[16]),"+f"(d[17]),"+f"(d[18]),"+f"(d[19]),"+f"(d[20]),"+f"(d[21]),"+f"(d[22]),"+f"(d[23]),"+f"(d[24]),"+f"(d[25]),"+f"(d[26]),"+f"(d[27]),"+f"(d[28]),"+f"(d[29]),"+f"(d[30]),"+f"(d[31]),"+f"(d[32]),"+f"(d[33]),"+f"(d[34]),"+f"(d[35]),"+f"(d[36]),"+f"(d[37]),"+f"(d[38]),"+f"(d[39]),"+f"(d[40]),"+f"(d[41]),"+f"(d[42]),"+f"(d[43]),"+f"(d[44]),"+f"(d[45]),"+f"(d[46]),"+f"(d[47]),"+f"(d[48]),"+f"(d[49]),"+f"(d[50]),"+f"(d[51]),"+f"(d[52]),"+f"(d[53]),"+f"(d[54]),"+f"(d[55]),"+f"(d[56]),"+f"(d[57]),"+f"(d[58]),"+f"(d[59]),"+f"(d[60]),"+f"(d[61]),"+f"(d[62]),"+f"(d[63]) : "l"(a),"l"(b),"r"(acc));
}
__device__ __forceinline__ void mma_ss_t64(float (&d)[32], uint64_t a, uint64_t b, int acc) {
  asm volatile("{\n.reg .pred p;\nsetp.ne.b32 p, %34, 0;\n"
    "wgmma.mma_async.sync.aligned.m64n64k16.f32.bf16.bf16 {%0,%1,%2,%3,%4,%5,%6,%7,%8,%9,%10,%11,%12,%13,%14,%15,%16,%17,%18,%19,%20,%21,%22,%23,%24,%25,%26,%27,%28,%29,%30,%31}, %32, %33, p, 1, 1, 0, 1;\n}\n"
    : "+f"(d[0]),"+f"(d[1]),"+f"(d[2]),"+f"(d[3]),"+f"(d[4]),"+f"(d[5]),"+f"(d[6]),"+f"(d[7]),"+f"(d[8]),"+f"(d[9]),"+f"(d[10]),"+f"(d[11]),"+f"(d[12]),"+f"(d[13]),"+f"(d[14]),"+f"(d[15]),"+f"(d[16]),"+f"(d[17]),"+f"(d[18]),"+f"(d[19]),"+f"(d[20]),"+f"(d[21]),"+f"(d[22]),"+f"(d[23]),"+f"(d[24]),"+f"(d[25]),"+f"(d[26]),"+f"(d[27]),"+f"(d[28]),"+f"(d[29]),"+f"(d[30]),"+f"(d[31]) : "l"(a),"l"(b),"r"(acc));
}
__device__ __forceinline__ void mma_ss_t24(float (&d)[12], uint64_t a, uint64_t b, int acc) {
  asm volatile("{\n.reg .pred p;\nsetp.ne.b32 p, %14, 0;\n"
    "wgmma.mma_async.sync.aligned.m64n24k16.f32.bf16.bf16 {%0,%1,%2,%3,%4,%5,%6,%7,%8,%9,%10,%11}, %12, %13, p, 1, 1, 0, 1;\n}\n"
    : "+f"(d[0]),"+f"(d[1]),"+f"(d[2]),"+f"(d[3]),"+f"(d[4]),"+f"(d[5]),"+f"(d[6]),"+f"(d[7]),"+f"(d[8]),"+f"(d[9]),"+f"(d[10]),"+f"(d[11]) : "l"(a),"l"(b),"r"(acc));
}

__device__ __forceinline__ uint32_t hfma2(uint32_t a, uint32_t b, uint32_t c) { uint32_t r; asm("fma.rn.f16x2 %0, %1, %2, %3;" : "=r"(r) : "r"(a), "r"(b), "r"(c)); return r; }
__device__ __forceinline__ uint32_t packh(float lo, float hi) { uint32_t r; asm("cvt.rn.f16x2.f32 %0, %1, %2;" : "=r"(r) : "f"(hi), "f"(lo)); return r; }
__device__ __forceinline__ void unpackh(uint32_t a, float& lo, float& hi) { asm("{\n.reg .b16 l, h;\nmov.b32 {l, h}, %2;\ncvt.f32.f16 %0, l;\ncvt.f32.f16 %1, h;\n}" : "=f"(lo), "=f"(hi) : "r"(a)); }
__device__ __forceinline__ uint32_t exp2_mufu(uint32_t s) { uint32_t r; asm("ex2.approx.f16x2 %0, %1;" : "=r"(r) : "r"(s)); return r; }
__device__ __forceinline__ uint32_t exp2_fma(uint32_t s) {
  uint32_t t, u;
  asm("fma.rn.relu.f16x2 %0, %1, %2, %3;" : "=r"(t) : "r"(s), "r"(0x02000200u), "r"(0x000a000au));
  asm("mul.rn.f16x2 %0, %1, %2;" : "=r"(u) : "r"(s), "r"(0x02000200u));
  const uint32_t f = hfma2(u, 0xF800F800u, s);
  const uint32_t y = hfma2(hfma2(f, 0x45614561u, 0x27f627f6u), f, 0x05aa05aau);
  return y + (t << 10);
}
template <int J> __device__ __forceinline__ void sm_unit(const uint32_t (&s)[16], uint32_t (&p)[4]) {
  p[0] = exp2_mufu(s[4 * J]); p[1] = exp2_fma(s[4 * J + 1]); p[2] = exp2_mufu(s[4 * J + 2]); p[3] = exp2_fma(s[4 * J + 3]);
}

#define KD(lo) mk64((lo), dhi(256, 3))
#define VO(x) ((uint32_t)(x) - ((uint32_t)(x) << 16))

__device__ __forceinline__ void flush(uint32_t (&a)[6], uint32_t (&o)[6]) {
#pragma unroll
  for (int i = 0; i < 6; i++) asm volatile("add.rn.f16x2 %0, %0, %1;" : "+r"(a[i]) : "r"(o[i]) : "memory");
}
__device__ __forceinline__ void attn_fast(const uint32_t (&q0)[4], const uint32_t (&q1)[4], uint32_t (&a0)[6], uint32_t (&a1)[6], int lane) {
  const uint32_t kvfull = sb + B_KVFULL, kvempty = sb + B_KVEMPTY;
  const uint32_t kbase = dlo(sb + KV_OFF, 16), vbase = dlo(sb + KV_OFF, ONES_OFF - KV_OFF);
  uint32_t s0[16] = {}, s1[16] = {}, o0[6] = {}, o1[6] = {};
  pinu(s0); pinu(s1); pinu(o0); pinu(o1);
  {
    uint32_t p0[4]={0,0,0,0}; pinu(p0);
    uint32_t p1[4]={0,0,0,0}; pinu(p1);
    uint32_t p2[4]={0,0,0,0}; pinu(p2);
    uint32_t p3[4]={0,0,0,0}; pinu(p3);
    wg_fence(); mma_qk(s0, q0, KD(kbase)); wg_commit(); wg_wait<0>(); pinu(s0);
    uint32_t vprev = vbase - VO(512);
#pragma unroll 1
    for (int it = 0; it < 8; it++) {
      const uint32_t sA = (it & 1) * 2, ph = (it >> 1) & 1, phn = ((it + 1) >> 1) & 1;
      const uint32_t kcur = kbase + sA * 512, knxt = kbase + (sA ^ 2) * 512, vcur = vbase + VO(sA * 512);
      wg_fence();
      mma_qk(s1,q1,KD(kcur+0));
      mma_pv0(o1,p2,KD(vprev+VO(960)));
      mma_pv(o1,p3,KD(vprev+VO(992)));
      wg_commit();
      flush(a0, o0);
      sm_unit<0>(s0,p0);
      sm_unit<1>(s0,p1);
      wg_fence();
      mma_pv0(o0,p0,KD(vcur+VO(128)));
      mma_pv(o0,p1,KD(vcur+VO(160)));
      wg_commit();
      wg_wait<1>();
      if (!(EXP & 32) && lane==0 && it!=0) mbar_arrive(kvempty+8*((sA^2)+1));
      sm_unit<2>(s0,p2);
      sm_unit<3>(s0,p3);
      wg_fence();
      mma_qk(s0,q0,KD(kcur+256));
      mma_pv(o0,p2,KD(vcur+VO(192)));
      mma_pv(o0,p3,KD(vcur+VO(224)));
      wg_commit();
      wg_wait<1>(); pinu(s1);
      sm_unit<0>(s1,p0);
      sm_unit<1>(s1,p1);
      wg_fence();
      mma_pv(o1,p0,KD(vcur+VO(128)));
      mma_pv(o1,p1,KD(vcur+VO(160)));
      wg_commit();
      wg_wait<1>();
      sm_unit<2>(s1,p2);
      sm_unit<3>(s1,p3);
      wg_fence();
      mma_qk(s1,q1,KD(kcur+256));
      mma_pv(o1,p2,KD(vcur+VO(192)));
      mma_pv(o1,p3,KD(vcur+VO(224)));
      wg_commit();
      wg_wait<1>(); pinu(s0);
      sm_unit<0>(s0,p0);
      sm_unit<1>(s0,p1);
      wg_fence();
      mma_pv(o0,p0,KD(vcur+VO(384)));
      mma_pv(o0,p1,KD(vcur+VO(416)));
      wg_commit();
      wg_wait<1>();
      sm_unit<2>(s0,p2);
      sm_unit<3>(s0,p3);
      if (!(EXP & 16)) mbar_wait(kvfull+8*(sA+1), ph);
      wg_fence();
      mma_qk(s0,q0,KD(kcur+512));
      mma_pv(o0,p2,KD(vcur+VO(448)));
      mma_pv(o0,p3,KD(vcur+VO(480)));
      wg_commit();
      wg_wait<1>(); pinu(s1);
      sm_unit<0>(s1,p0);
      sm_unit<1>(s1,p1);
      wg_fence();
      mma_pv(o1,p0,KD(vcur+VO(384)));
      mma_pv(o1,p1,KD(vcur+VO(416)));
      wg_commit();
      wg_wait<1>();
      sm_unit<2>(s1,p2);
      sm_unit<3>(s1,p3);
      wg_fence();
      mma_qk(s1,q1,KD(kcur+512));
      mma_pv(o1,p2,KD(vcur+VO(448)));
      mma_pv(o1,p3,KD(vcur+VO(480)));
      wg_commit();
      wg_wait<1>(); pinu(s0);
      sm_unit<0>(s0,p0);
      sm_unit<1>(s0,p1);
      wg_fence();
      mma_pv(o0,p0,KD(vcur+VO(640)));
      mma_pv(o0,p1,KD(vcur+VO(672)));
      wg_commit();
      wg_wait<1>();
      if (!(EXP & 32) && lane==0) mbar_arrive(kvempty+8*sA);
      sm_unit<2>(s0,p2);
      sm_unit<3>(s0,p3);
      wg_fence();
      mma_qk(s0,q0,KD(kcur+768));
      mma_pv(o0,p2,KD(vcur+VO(704)));
      mma_pv(o0,p3,KD(vcur+VO(736)));
      wg_commit();
      wg_wait<1>(); pinu(s1);
      sm_unit<0>(s1,p0);
      sm_unit<1>(s1,p1);
      wg_fence();
      mma_pv(o1,p0,KD(vcur+VO(640)));
      mma_pv(o1,p1,KD(vcur+VO(672)));
      wg_commit();
      wg_wait<1>();
      sm_unit<2>(s1,p2);
      sm_unit<3>(s1,p3);
      wg_fence();
      mma_qk(s1,q1,KD(kcur+768));
      mma_pv(o1,p2,KD(vcur+VO(704)));
      mma_pv(o1,p3,KD(vcur+VO(736)));
      wg_commit();
      wg_wait<1>(); pinu(s0);
      sm_unit<0>(s0,p0);
      sm_unit<1>(s0,p1);
      wg_fence();
      mma_pv(o0,p0,KD(vcur+VO(896)));
      mma_pv(o0,p1,KD(vcur+VO(928)));
      wg_commit();
      wg_wait<1>();
      sm_unit<2>(s0,p2);
      sm_unit<3>(s0,p3);
      if (!(EXP & 16)) mbar_wait(kvfull+8*(sA^2), phn);
      wg_fence();
      mma_qk(s0,q0,KD(knxt));
      mma_pv(o0,p2,KD(vcur+VO(960)));
      mma_pv(o0,p3,KD(vcur+VO(992)));
      wg_commit();
      wg_wait<1>(); pinu(s1);
      sm_unit<0>(s1,p0);
      sm_unit<1>(s1,p1);
      wg_fence();
      mma_pv(o1,p0,KD(vcur+VO(896)));
      mma_pv(o1,p1,KD(vcur+VO(928)));
      wg_commit();
      wg_wait<1>();
      sm_unit<2>(s1,p2);
      sm_unit<3>(s1,p3);
      wg_wait<0>(); pinu(s0); pinu(o0); pinu(o1);
      flush(a1, o1);
      vprev = vcur;
    }
    wg_fence();
    mma_pv0(o1,p2,KD(vprev+VO(960)));
    mma_pv(o1,p3,KD(vprev+VO(992)));
    wg_commit(); flush(a0, o0); wg_wait<0>(); pinu(o1);
    if (lane == 0) mbar_arrive(kvempty + 8 * 3);
    flush(a1, o1);
  }
}

__device__ __forceinline__ void mma16816(float* d, const uint32_t (&a)[4], uint32_t b0, uint32_t b1) {
  asm("mma.sync.aligned.m16n8k16.row.col.f32.bf16.bf16.f32 {%0,%1,%2,%3}, {%4,%5,%6,%7}, {%8,%9}, {%0,%1,%2,%3};"
      : "+f"(d[0]), "+f"(d[1]), "+f"(d[2]), "+f"(d[3]) : "r"(a[0]), "r"(a[1]), "r"(a[2]), "r"(a[3]), "r"(b0), "r"(b1));
}
__device__ __forceinline__ uint32_t trans8(uint32_t a) { uint32_t r; asm("movmatrix.sync.aligned.m8n8.trans.b16 %0, %1;" : "=r"(r) : "r"(a)); return r; }
__device__ __forceinline__ void attn_online(const uint32_t (&qn)[4], float g0, float g1, uint8_t* dst, int lane) {
  uint32_t q[4];
#pragma unroll
  for (int i = 0; i < 4; i++) {
    const int src = (lane & ~3) | ((2 * lane + (i >> 1)) & 3);
    const uint32_t u = __shfl_sync(~0u, qn[i & 1], src), v = __shfl_sync(~0u, qn[2 + (i & 1)], src);
    q[i] = (lane & 2) ? v : u;
  }
  float o[12] = {};
  float m0 = -3e38f, m1 = -3e38f;
#pragma unroll 2
  for (int b = 0; b < 128; b++) {
    const uint4 k = __ldcg(g_kvb + b * 64 + lane), v = __ldcg(g_kvb + b * 64 + 32 + lane);
    float s[8] = {};
    mma16816(s, q, k.x, k.z); mma16816(s + 4, q, k.y, k.w);
    float x = fmaxf(fmaxf(m0, fmaxf(s[0], s[1])), fmaxf(s[4], s[5])), y = fmaxf(fmaxf(m1, fmaxf(s[2], s[3])), fmaxf(s[6], s[7]));
    x = fmaxf(x, __shfl_xor_sync(~0u, x, 1)); x = fmaxf(x, __shfl_xor_sync(~0u, x, 2));
    y = fmaxf(y, __shfl_xor_sync(~0u, y, 1)); y = fmaxf(y, __shfl_xor_sync(~0u, y, 2));
    const float cx = ex2((m0 - x) * QS), cy = ex2((m1 - y) * QS);
    m0 = x; m1 = y;
#pragma unroll
    for (int j = 0; j < 3; j++) { o[4 * j] *= cx; o[4 * j + 1] *= cx; o[4 * j + 2] *= cy; o[4 * j + 3] *= cy; }
    const uint32_t p[4] = {pack2(ex2((s[0] - x) * QS), ex2((s[1] - x) * QS)), pack2(ex2((s[2] - y) * QS), ex2((s[3] - y) * QS)),
                           pack2(ex2((s[4] - x) * QS), ex2((s[5] - x) * QS)), pack2(ex2((s[6] - y) * QS), ex2((s[7] - y) * QS))};
    mma16816(o, p, trans8(v.x), trans8(v.y)); mma16816(o + 4, p, trans8(v.z), trans8(v.w)); mma16816(o + 8, p, 0x3F803F80u, 0x3F803F80u);
  }
  const float a = __fdividef(g0, o[8]), b = __fdividef(g1, o[10]);
  dst += (lane & 2) * 508 + (lane & 1) * 4;
  stg64(dst, pack2(o[0] * a, o[1] * a), pack2(o[4] * a, o[5] * a));
  stg64(dst + 128, pack2(o[2] * b, o[3] * b), pack2(o[6] * b, o[7] * b));
}

__device__ __forceinline__ void store_o(const float (&o)[12], float g0, float g1, uint8_t* dst) {
  const float a = __fdividef(g0, o[8]), b = __fdividef(g1, o[10]);
  stg32(dst, pack2(o[0] * a, o[1] * a));
  stg32(dst + 128, pack2(o[2] * b, o[3] * b));
  stg32(dst + 1024, pack2(o[4] * a, o[5] * a));
  stg32(dst + 1152, pack2(o[6] * b, o[7] * b));
}

__device__ __forceinline__ void attn_passes(uint32_t (&qh)[4][4], uint32_t (&qb)[4][4], float qn, uint8_t* odst, uint32_t* oflag, int wg) {
  const int lane = threadIdx.x & 31;
#pragma unroll 1
  for (int p = 0; p < 2; p++) {
    {
      uint32_t a0[6] = {}, a1[6] = {};
      attn_fast(qh[0], qh[1], a0, a1, lane);
      mbar_wait(sb + B_GREADY, 0);
      const uint32_t ga = sb + G_OFF + ((threadIdx.x >> 5) * 16 + (lane >> 2)) * 8;
      const float g0 = __uint_as_float(lds32(ga)), g1 = __uint_as_float(lds32(ga + 64));
      float o0[12], o1[12], hi = 0.f;
#pragma unroll
      for (int i = 0; i < 6; i++) { unpackh(a0[i], o0[2 * i], o0[2 * i + 1]); unpackh(a1[i], o1[2 * i], o1[2 * i + 1]); }
      store_o(o0, g0, g1, odst);
      store_o(o1, g0, g1, odst + 2048);
      const float kn = __uint_as_float(lds32(sb + MISC_OFF + 32));
      const float lo = fminf(fminf(o0[8], o0[10]), fminf(o1[8], o1[10]));
#pragma unroll
      for (int i = 0; i < 11; i++) hi += fabsf(o0[i]) + fabsf(o1[i]);
      const bool ok = !FORCE_SLOW && qn * kn <= 372.f && qn <= 65536.f && kn <= 65536.f && lo >= 128.f && hi < INFINITY;
      if (!__all_sync(~0u, ok)) {
        __syncwarp();
#pragma unroll 1
        for (int h = 0; h < 2; h++) {
          attn_online(qb[0], g0, g1, odst + h * 2048, lane);
#pragma unroll
          for (int i = 0; i < 4; i++) qb[0][i] = qb[1][i];
        }
      }
    }
    if (p == 0) {
      __syncwarp();
      if (lane == 0) mbar_arrive(sb + B_PUB + 32);
    } else {
      bar_sync(1 + wg);
      if ((threadIdx.x & 127) == 0) { fence_gpu(); st_rlx(oflag, 1); }
    }
    odst += 32 * 1024;
#pragma unroll
    for (int i = 0; i < 4; i++) { qh[0][i] = qh[2][i]; qh[1][i] = qh[3][i]; qb[0][i] = qb[2][i]; qb[1][i] = qb[3][i]; }
  }
}

__device__ __forceinline__ float geglu(float x, float u, float c) {
  const float y = x * fmaf(x * x, 0.044715f * 0.7978845608028654f, 0.7978845608028654f);
  float t; asm("tanh.approx.f32 %0, %1;" : "=f"(t) : "f"(y));
  const float h = x * u * c;
  return fmaf(h, t, h);
}
__device__ __forceinline__ void store_h(const float (&d)[64], float c0, float c1, uint8_t* dst) {
#pragma unroll
  for (int j = 0; j < 8; j++) {
    stg32(dst + j * 1024, pack2(geglu(d[4 * j], d[32 + 4 * j], c0), geglu(d[4 * j + 1], d[33 + 4 * j], c0)));
    stg32(dst + j * 1024 + 128, pack2(geglu(d[4 * j + 2], d[34 + 4 * j], c1), geglu(d[4 * j + 3], d[35 + 4 * j], c1)));
  }
}

__global__ void __launch_bounds__(512, 1)
fused_kernel(const __grid_constant__ Maps mp, const uint16_t* __restrict__ gate_w, const uint4* __restrict__ wk, const uint4* __restrict__ wv,
             const uint8_t* __restrict__ wd_raw, const uint8_t* __restrict__ wo_raw) {
  extern __shared__ __align__(1024) uint8_t smem[];
  const int tid = threadIdx.x, lane = tid & 31;
  const int warp = __shfl_sync(~0u, tid >> 5, 0);
  const int wg = warp >> 2, wq4 = warp & 3;
  const int tb = blockIdx.x >> 3, cg = blockIdx.x & 7;
  const int half = cg & 1;

  if (warp == 12) {
    if (lane == 0) {
      EV(0);
      if ((uint32_t)__cvta_generic_to_shared(smem) != sb) __trap();
      for (int i = 0; i < 8; i++) mbar_init(sb + B_XFULL + 8 * i, 1);
      for (int i = 0; i < 4; i++) mbar_init(sb + B_WQ + 8 * i, 1);
      asm volatile("fence.mbarrier_init.release.cluster;" ::: "memory");
    }
    __syncwarp();
    const uint32_t xb = sb + B_XFULL + 32 * half, xd = sb + X_OFF + half * 65536;
    const int row = tb * 128 + half * 64;
    if (cg < 4) {
#pragma unroll
      for (int j = 0; j < 4; j++) u_tma3d(xb + 8 * j, 16384, xd + j * 16384, &mp.x, 0, row, 2 * j);
    }
#pragma unroll
    for (int j = 0; j < 4; j++) {
      u_tma2d(sb + B_WQ + 8 * j, 16384, sb + W_OFF + j * 16384, &mp.wq, cg * 64, j * 128);
      u_tma3d((xb ^ 32) + 8 * j, 16384, (xd ^ 65536) + j * 16384, &mp.x, 0, row ^ 64, 2 * j);
      if (cg >= 4) u_tma3d(xb + 8 * j, 16384, xd + j * 16384, &mp.x, 0, row, 2 * j);
    }
  } else if (tid == 416) {
    mbar_init(sb + B_GREADY, 1); mbar_init(sb + B_FFN1, 4);
    for (int i = 0; i < 4; i++) { mbar_init(sb + B_WFULL + 8 * i, 1); mbar_init(sb + B_WEMPTY + 8 * i, 8); mbar_init(sb + B_KVFULL + 8 * i, 1); mbar_init(sb + B_KVEMPTY + 8 * i, 8); mbar_init(sb + B_PUB + 8 * i, 4); }
    mbar_init(sb + B_PUB + 32, 8);
    for (int i = 0; i < 8; i++) { mbar_init(sb + B_FFULL + 8 * i, 2); mbar_init(sb + B_FEMPTY + 8 * i, 4); }
    asm volatile("fence.mbarrier_init.release.cluster;" ::: "memory");
  } else if (tid == 448) {
    asm volatile("prefetch.tensormap [%0];" ::"l"(&mp.wg) : "memory");
    asm volatile("prefetch.tensormap [%0];" ::"l"(&mp.wu) : "memory");
    asm volatile("prefetch.tensormap [%0];" ::"l"(&mp.wd) : "memory");
    asm volatile("prefetch.tensormap [%0];" ::"l"(&mp.wo) : "memory");
    asm volatile("prefetch.tensormap [%0];" ::"l"(&mp.out) : "memory");
  }
  uint4 wa[4], wb[4];
  uint32_t wz[4];
  if (cg < 4 && wg == half) {
    const uint4* w = (cg < 2 ? wk : wv) + (tid & 127) * 2;
#pragma unroll
    for (int i = 0; i < 4; i++) { wa[i] = __ldg(w + i * 256); wb[i] = __ldg(w + i * 256 + 1); wz[i] = __ldg(gate_w + (tid & 127) + i * 128); }
  }
  if (tid < 128) { sts32(sb + ONES_OFF + tid * 4, 0x3C003C00u); asm volatile("fence.proxy.async.shared::cta;" ::: "memory"); }
  __syncthreads();
  if (tid == 0) EV(1);

  uint8_t* const a_tb = g_a + (size_t)(tb * 2) * A_BYTES;
  uint32_t* const fl_tb = g_flags + 64 + tb * 128;

  if (wg == 3) {
    asm volatile("setmaxnreg.dec.sync.aligned.u32 %0;" ::"n"(REG_PROD));
    if (wq4 == 0) {
#pragma unroll 1
      for (int n = 0; n < 32; n++) {
        const int s = n & 3;
        const int hc = n < 24 ? (n & 24) + cg : 24 + (cg >> 1);
        mbar_wait_sleep<NS_W>(sb + B_WEMPTY + 8 * s, (n >> 2) & 1);
        u_tma2d_pair(sb + B_WFULL + 8 * s, sb + W_OFF + s * 16384, &mp.wg, &mp.wu, hc * 64, (n & 7) * 64, (n & 7) * 64);
        if (n == 8) { u_prefetch(wd_raw + blockIdx.x * 14336, 14336); u_prefetch(wo_raw + blockIdx.x * 4096, 4096); }
      }
      mbar_wait_sleep<NS_W>(sb + B_FFN1, 0);
#pragma unroll 1
      for (int n = 0; n < 36; n++) {
        const int s = n & 7;
        mbar_wait_sleep<NS_W>(sb + B_FEMPTY + 8 * s, ((n >> 3) & 1) ^ 1);
        u_tma4d(sb + B_FFULL + 8 * s, 16384, sb + s * FST + 8192, n < 28 ? &mp.wd : &mp.wo, n & 32, n < 28 ? 2 * n : 2 * (n & 3), cg & 6);
      }
    } else if (wq4 == 1) {
      if (cg < 4) asm volatile("bar.sync 4, 192;" ::: "memory");
      uint32_t todo = 0x55555555u, rdy = 0;
#pragma unroll 1
      for (int n = 0; n < 33; n++) {
        if (n <= 4 && (n == 4 || !(rdy & todo))) {
          uint64_t f;
          for (int i = 0;; i++) {
            f = ld_acq64(g_flags + 2 * lane);
            rdy = __ballot_sync(~0u, (uint32_t)f != 0 && (f >> 32) != 0);
            rdy &= rdy >> 1;
            if (n == 4 ? (~rdy & 0x55555555u) == 0 : (rdy & todo) != 0) break;
            if (i > 0x100000) __trap();
          }
          fence_async_gl();
          if (n == 4) {
            const uint32_t fk = __reduce_max_sync(~0u, max((uint32_t)f, (uint32_t)(f >> 32)));
            if (lane == 0) sts32(sb + MISC_OFF + 32, fk);
            __syncwarp();
            u_bulk(sb + B_GREADY, 1024, sb + G_OFF, g_gate + tb * 128);
          }
        }
        const int c = __ffs(rdy & todo) - 1, s = n & 3;
        todo ^= 1u << c;
        if (!todo) todo = 0x55555555u;
        mbar_wait_sleep<NS_KV>(sb + B_KVEMPTY + 8 * s, ((n >> 2) & 1) ^ 1);
        u_bulk(sb + B_KVFULL + 8 * s, 8192, sb + KV_OFF + s * 8192, g_kv + c * 4096);
      }
    } else if (wq4 == 3) {
      if (cg < 4) {
        asm volatile("bar.sync 4, 192;" ::: "memory");
        const uint32_t m = max(max(lds32(sb + MISC_OFF + 48), lds32(sb + MISC_OFF + 52)), max(lds32(sb + MISC_OFF + 56), lds32(sb + MISC_OFF + 60)));
        fence_gpu();
        if (lane == 0) { st_rlx(g_flags + (tb * 2 + half) * 2 + (cg >> 1), m | 1); EV(2); }
      }
#pragma unroll 1
      for (int e = 0; e < 5; e++) {
        mbar_wait_sleep<NS_W>(sb + B_PUB + 8 * e, 0);
        fence_gpu();
        const int idx = e < 3 ? 2 * (e * 8 + cg) : e == 3 ? 2 * (24 + (cg >> 1)) : 2 * cg + 1;
        if (lane < 2 && (e != 3 || lane == half)) st_rlx(fl_tb + lane * 64 + idx, 1);
      }
    } else {
      mbar_wait_sleep<NS_W>(sb + B_FFN1, 0);
      const uint32_t* fl = fl_tb + half * 64 + 2 * lane;
      const uint8_t* src = a_tb + half * A_BYTES;
      int ready = 0;
#pragma unroll 1
      for (int n = 0; n < 36; n++) {
        if (n >= ready) {
          for (int i = 0;; i++) {
            const uint64_t f = ld_acq64(fl);
            const uint32_t rh = __ballot_sync(~0u, (uint32_t)f != 0), ro = __ballot_sync(~0u, (f >> 32) != 0);
            ready = __ffs(~rh) - 1;
            if (ready == 28) ready += (__ffs(~ro) - 1) >> 1;
            if (n < ready) break;
            if (i > 0x100000) __trap();
            __nanosleep(NS_F);
          }
          fence_async_gl();
        }
        const int s = n & 7;
        mbar_wait_sleep<NS_W>(sb + B_FEMPTY + 8 * s, ((n >> 3) & 1) ^ 1);
        u_bulk(sb + B_FFULL + 8 * s, 8192, sb + s * FST, src + n * 8192);
      }
      uint32_t last = 0;
      if (lane == 0) { __threadfence(); last = atomicAdd(&g_done, 1) == gridDim.x - 1; __threadfence(); }
      if (__shfl_sync(~0u, last, 0)) {
        for (int i = lane; i < (64 + 32 * 64) / 4; i += 32) reinterpret_cast<uint4*>(g_flags)[i] = make_uint4(0, 0, 0, 0);
        if (lane == 0) g_done = 0;
      }
    }
  } else if (wg == 2) {
    asm volatile("setmaxnreg.inc.sync.aligned.u32 %0;" ::"n"(REG_GEMM));
    float d0[64], d1[64];
    zero(d0); zero(d1);
    const uint32_t xl = dlo(sb + X_OFF, 16), wl = dlo(sb + W_OFF, 8192);
    constexpr uint32_t H128 = dhi(1024, 1);
    uint8_t* const hdst = a_tb + wq4 * 256 + lane * 4;
    const uint32_t grow = sb + G_OFF + (wq4 * 16 + (lane >> 2)) * 8 + 4;
#pragma unroll 1
    for (int st = 0; st < 3; st++) {
#pragma unroll 1
      for (int kc = 0; kc < 8; kc++) {
        const int s = kc & 3;
        if (st == 0) { mbar_wait(sb + B_XFULL + 8 * (kc >> 1), 0); mbar_wait(sb + B_XFULL + 32 + 8 * (kc >> 1), 0); }
        mbar_wait(sb + B_WFULL + 8 * s, (kc >> 2) & 1);
        const uint32_t a = xl + kc * 512, b = wl + s * 1024;
#pragma unroll
        for (int k = 0; k < 4; k++) {
          wg_fence();
          mma_ss_t128(d0, mk64(a + 2 * k, H128), mk64(b + 128 * k, H128), (kc | k) != 0);
          mma_ss_t128(d1, mk64(a + 4096 + 2 * k, H128), mk64(b + 128 * k, H128), (kc | k) != 0);
          wg_commit(); wg_wait<GW1>();
          if (GW1 && k == 0 && kc != 0 && lane == 0) mbar_arrive2(sb + B_WEMPTY + 8 * ((s + 3) & 3));
        }
        if (!GW1 && lane == 0) mbar_arrive2(sb + B_WEMPTY + 8 * s);
      }
      if (GW1) { wg_wait<0>(); if (lane == 0) mbar_arrive2(sb + B_WEMPTY + 8 * 3); }
      pin(d0); pin(d1);
      if (st == 0) { if (tid == 256) EV(8); mbar_wait(sb + B_GREADY, 0); }
      const int hc = st * 8 + cg;
      store_h(d0, __uint_as_float(lds32(grow)), __uint_as_float(lds32(grow + 64)), hdst + hc * 8192);
      store_h(d1, __uint_as_float(lds32(grow + 512)), __uint_as_float(lds32(grow + 576)), hdst + A_BYTES + hc * 8192);
      __syncwarp();
      if (lane == 0) mbar_arrive(sb + B_PUB + 8 * st);
      pin(d0); pin(d1);
    }
    {
#pragma unroll 1
      for (int kc = 0; kc < 8; kc++) {
        const int s = kc & 3;
        mbar_wait(sb + B_WFULL + 8 * s, (kc >> 2) & 1);
        const uint32_t a = xl + kc * 512 + half * 4096, b = wl + s * 1024;
#pragma unroll
        for (int k = 0; k < 4; k += 2) {
          wg_fence();
          mma_ss_t128(d0, mk64(a + 2 * k, H128), mk64(b + 128 * k, H128), (kc | k) != 0);
          mma_ss_t128(d0, mk64(a + 2 * k + 2, H128), mk64(b + 128 * k + 128, H128), 1);
          wg_commit(); wg_wait<GW1>();
          if (GW1 && k == 0 && kc != 0 && lane == 0) mbar_arrive2(sb + B_WEMPTY + 8 * ((s + 3) & 3));
        }
        if (!GW1 && lane == 0) mbar_arrive2(sb + B_WEMPTY + 8 * s);
      }
      wg_wait<0>();
      pin(d0);
      if (lane == 0) mbar_arrive(sb + B_FFN1);
      if (tid == 256) EV(12);
      const int hc = 24 + (cg >> 1);
      store_h(d0, __uint_as_float(lds32(grow + half * 512)), __uint_as_float(lds32(grow + half * 512 + 64)), hdst + half * A_BYTES + hc * 8192);
      __syncwarp();
      if (lane == 0) mbar_arrive(sb + B_PUB + 24);
      pin(d0);
    }
    const uint32_t al = dlo(sb, 1024), bl = dlo(sb + 8192, 8192);
    constexpr uint32_t HA = dhi(128, 0);
#pragma unroll 1
    for (int n = 0; n < 36; n++) {
      const int s = n & 7;
      mbar_wait_sleep<NS_G>(sb + B_FFULL + 8 * s, (n >> 3) & 1);
      const uint32_t a = al + s * (FST >> 4), b = bl + s * (FST >> 4);
#pragma unroll
      for (int k = 0; k < 4; k += 2) {
        wg_fence();
        mma_ss_t128(d0, mk64(a + 128 * k, HA), mk64(b + 128 * k, H128), (n | k) != 0);
        mma_ss_t128(d0, mk64(a + 128 * k + 128, HA), mk64(b + 128 * k + 128, H128), 1);
        wg_commit(); wg_wait<GW2>();
        if (GW2 && k == 0 && n != 0 && lane == 0) mbar_arrive(sb + B_FEMPTY + 8 * ((s + 7) & 7));
      }
      if (!GW2 && lane == 0) mbar_arrive(sb + B_FEMPTY + 8 * s);
    }
    wg_wait<0>();
    pin(d0);
    if (tid == 256) EV(19);
    const uint32_t stg = sb + 4 * FST;
    const int r = wq4 * 16 + (lane & 7) + ((lane >> 3) & 1) * 8;
#pragma unroll
    for (int j = 0; j < 8; j++) {
      const int c16 = (2 * j + (lane >> 4)) & 7;
      const uint32_t ad = stg + (j >> 2) * 8192 + r * 128 + ((c16 ^ (r & 7)) << 4);
      asm volatile("stmatrix.sync.aligned.m8n8.x4.shared.b16 [%0], {%1,%2,%3,%4};" ::"r"(ad), "r"(pack2(d0[8 * j], d0[8 * j + 1])), "r"(pack2(d0[8 * j + 2], d0[8 * j + 3])),
                   "r"(pack2(d0[8 * j + 4], d0[8 * j + 5])), "r"(pack2(d0[8 * j + 6], d0[8 * j + 7])) : "memory");
    }
    asm volatile("fence.proxy.async.shared::cta;" ::: "memory");
    bar_sync(3);
    if (tid == 256) {
      asm volatile("cp.async.bulk.tensor.3d.global.shared::cta.bulk_group [%0, {%2, %3, %4}], [%1];" ::"l"(&mp.out), "r"(stg), "r"(0), "r"(tb * 128 + half * 64), "r"(cg & 6) : "memory");
      asm volatile("cp.async.bulk.commit_group;" ::: "memory");
      asm volatile("cp.async.bulk.wait_group.read 0;" ::: "memory");
      EV(20);
    }
  } else {
    asm volatile("setmaxnreg.inc.sync.aligned.u32 %0;" ::"n"(REG_ATT));
    constexpr uint32_t H128 = dhi(1024, 1);
    const uint32_t xl = dlo(sb + X_OFF + wg * 65536, 16);
    if (cg < 4 && wg == half) {
#pragma unroll
      for (int i = 0; i < 4; i++) {
        const uint32_t a = sb + KV_OFF + i * 4096 + (tid & 127) * 32 + (tid & 4) * 4;
        sts128(a, wa[i].x, wa[i].z, wb[i].x, wb[i].z); sts128(a ^ 16, wa[i].y, wa[i].w, wb[i].y, wb[i].w); sts32(a + 16384, wz[i]);
      }
      asm volatile("fence.proxy.async.shared::cta;" ::: "memory");
      float d[12];
      zero(d);
      bar_sync(1 + wg);
      const uint32_t wl = dlo(sb + KV_OFF, 16384);
#pragma unroll 1
      for (int j = 0; j < 4; j++) {
        mbar_wait(sb + B_XFULL + 32 * wg + 8 * j, 0);
        wg_fence();
#pragma unroll
        for (int k = 0; k < 8; k++) mma_ss_t24(d, mk64(xl + j * 1024 + (k >> 2) * 512 + 2 * (k & 3), H128), KD(wl + j * 256 + 32 * k), 1);
        wg_commit();
      }
      wg_wait<0>(); pin(d);
      if ((tid & 127) == 0) EV(46);
      const float sc = cg < 2 ? 0.0625f : 1.f;
      uint8_t* dst = g_kv + (tb * 2 + wg) * 4096 + (cg >> 1) * 2048 + wq4 * 512 + ((lane * 8) ^ (lane & 16));
      stg64(dst, packh(d[0] * sc, d[1] * sc), packh(d[4] * sc, d[5] * sc));
      stg64(dst + 256, packh(d[2] * sc, d[3] * sc), packh(d[6] * sc, d[7] * sc));
      g_kvb[(tb * 8 + warp) * 64 + (cg >> 1) * 32 + lane] = make_uint4(pack2(d[0], d[1]), pack2(d[2], d[3]), pack2(d[4], d[5]), pack2(d[6], d[7]));
      uint32_t mx;
      if (cg < 2) {
        const float z0 = __shfl_sync(~0u, d[8], (lane & 7) * 4), z1 = __shfl_sync(~0u, d[10], (lane & 7) * 4);
        const float g = 1.f / (1.f + __expf((lane & 8) ? -z1 : -z0));
        if (lane < 16) g_gate[tb * 128 + warp * 16 + lane] = make_float2(g, 0.5f * (1.f - g));
        float n0 = sq4(d[0], d[1], d[4], d[5]), n1 = sq4(d[2], d[3], d[6], d[7]);
        n0 += __shfl_xor_sync(~0u, n0, 1); n1 += __shfl_xor_sync(~0u, n1, 1);
        n0 += __shfl_xor_sync(~0u, n0, 2); n1 += __shfl_xor_sync(~0u, n1, 2);
        mx = __reduce_max_sync(~0u, max(__float_as_uint(n0), __float_as_uint(n1)));
      } else {
        bool ok = true;
#pragma unroll
        for (int i = 0; i < 4; i++) {
          const int j = (i & 1) + (i >> 1) * 4;
          uint32_t c = max(__float_as_uint(d[j]) & 0x7fffffffu, __float_as_uint(d[j + 2]) & 0x7fffffffu);
          c = max(c, __shfl_xor_sync(~0u, c, 4)); c = max(c, __shfl_xor_sync(~0u, c, 8)); c = max(c, __shfl_xor_sync(~0u, c, 16));
          ok = ok && (c == 0 || (c >= 0x37800000u && c <= 0x47000000u));
        }
        mx = __all_sync(~0u, ok) ? 0 : 0x7f800001u;
      }
      if (lane == 0) sts32(sb + MISC_OFF + 48 + wq4 * 4, mx);
      asm volatile("bar.arrive 4, 192;" ::: "memory");
      if ((tid & 127) == 0) EV(47);
    }
    uint32_t qh[4][4], qb[4][4];
    float qn;
    {
      float d[32];
      zero(d);
      const uint32_t wl = dlo(sb + W_OFF, 8192);
#pragma unroll 1
      for (int s = 0; s < 4; s++) {
        mbar_wait(sb + B_XFULL + 32 * wg + 8 * s, 0);
        mbar_wait(sb + B_WQ + 8 * s, 0);
        wg_fence();
#pragma unroll
        for (int k = 0; k < 8; k++) mma_ss_t64(d, mk64(xl + (2 * s + (k >> 2)) * 512 + 2 * (k & 3), H128), mk64(wl + s * 1024 + 128 * k, H128), 1);
        wg_commit(); wg_wait<0>();
        if (lane == 0) mbar_arrive(sb + B_WEMPTY + 8 * s);
      }
      pin(d);
      if (tid == 0) EV(44);
      uint32_t nm = 0;
#pragma unroll
      for (int h = 0; h < 4; h++) {
        const float* dh = d + 8 * h;
#pragma unroll
        for (int i = 0; i < 4; i++) {
          const float c = (i & 1) ? QS / 32.f : QS * 16.f;
          qh[h][i] = packh(dh[2 * i] * c, dh[2 * i + 1] * c);
          qb[h][i] = pack2(dh[2 * i], dh[2 * i + 1]);
        }
        float n0 = sq4(dh[0], dh[1], dh[4], dh[5]), n1 = sq4(dh[2], dh[3], dh[6], dh[7]);
        n0 += __shfl_xor_sync(~0u, n0, 1); n1 += __shfl_xor_sync(~0u, n1, 1);
        n0 += __shfl_xor_sync(~0u, n0, 2); n1 += __shfl_xor_sync(~0u, n1, 2);
        nm = max(nm, max(__float_as_uint(n0), __float_as_uint(n1)));
      }
      qn = __uint_as_float(nm) * (QS * QS);
    }
    if (tid == 0) EV(3);
    mbar_wait(sb + B_KVFULL, 0);
    if (tid == 0) { EV(5); EVC(0); }
    uint8_t* odst = a_tb + wg * A_BYTES + (224 + cg * 4) * 1024 + wq4 * 256 + lane * 4;
    uint32_t* const oflag = fl_tb + wg * 64 + 2 * (8 + cg) + 1;
    attn_passes(qh, qb, qn, odst, oflag, wg);
  }
}

typedef CUresult (*EncodeFn)(CUtensorMap*, CUtensorMapDataType, cuuint32_t, void*, const cuuint64_t*, const cuuint64_t*, const cuuint32_t*, const cuuint32_t*,
                             CUtensorMapInterleave, CUtensorMapSwizzle, CUtensorMapL2promotion, CUtensorMapFloatOOBfill);

void make_map(EncodeFn fn, CUtensorMap* m, const void* p, uint64_t cols, uint64_t rows, uint32_t bc, uint32_t br, CUtensorMapSwizzle sw) {
  cuuint64_t dims[2] = {cols, rows}, strides[1] = {cols * 2};
  cuuint32_t box[2] = {bc, br}, es[2] = {1, 1};
  fn(m, CU_TENSOR_MAP_DATA_TYPE_BFLOAT16, 2, const_cast<void*>(p), dims, strides, box, es, CU_TENSOR_MAP_INTERLEAVE_NONE, sw,
     CU_TENSOR_MAP_L2_PROMOTION_L2_128B, CU_TENSOR_MAP_FLOAT_OOB_FILL_NONE);
}

void make_map3(EncodeFn fn, CUtensorMap* m, const void* p, uint64_t bw, uint64_t nblk, uint64_t rows, uint32_t bc, uint32_t br, CUtensorMapSwizzle sw) {
  cuuint64_t dims[3] = {bw, rows, nblk}, strides[2] = {bw * nblk * 2, bw * 2};
  cuuint32_t box[3] = {bc, br, 2}, es[3] = {1, 1, 1};
  fn(m, CU_TENSOR_MAP_DATA_TYPE_BFLOAT16, 3, const_cast<void*>(p), dims, strides, box, es, CU_TENSOR_MAP_INTERLEAVE_NONE, sw,
     CU_TENSOR_MAP_L2_PROMOTION_L2_128B, CU_TENSOR_MAP_FLOAT_OOB_FILL_NONE);
}

void make_map4(EncodeFn fn, CUtensorMap* m, const void* p, uint64_t rows, uint64_t rg) {
  cuuint64_t dims[4] = {64, rg, rows / rg, 8}, strides[3] = {1024, rg * 1024, 128};
  cuuint32_t box[4] = {64, 32, 2, 2}, es[4] = {1, 1, 1, 1};
  fn(m, CU_TENSOR_MAP_DATA_TYPE_BFLOAT16, 4, const_cast<void*>(p), dims, strides, box, es, CU_TENSOR_MAP_INTERLEAVE_NONE, CU_TENSOR_MAP_SWIZZLE_128B,
     CU_TENSOR_MAP_L2_PROMOTION_L2_128B, CU_TENSOR_MAP_FLOAT_OOB_FILL_NONE);
}

}

extern "C" void kernel_launch(void* const* d_in, const int* in_sizes, int n_in, void* d_out, int out_size) {
  void* fp = nullptr;
  cudaDriverEntryPointQueryResult qr;
  cudaGetDriverEntryPoint("cuTensorMapEncodeTiled", &fp, cudaEnableDefault, &qr);
  EncodeFn fn = (EncodeFn)fp;
  Maps mp;
  make_map3(fn, &mp.x, d_in[0], 64, 8, S_, 64, 64, CU_TENSOR_MAP_SWIZZLE_128B);
  make_map(fn, &mp.wq, d_in[1], D_, D_, 64, 128, CU_TENSOR_MAP_SWIZZLE_128B);
  make_map4(fn, &mp.wo, d_in[4], D_, 64);
  make_map(fn, &mp.wg, d_in[6], F_, D_, 64, 64, CU_TENSOR_MAP_SWIZZLE_128B);
  make_map(fn, &mp.wu, d_in[7], F_, D_, 64, 64, CU_TENSOR_MAP_SWIZZLE_128B);
  make_map4(fn, &mp.wd, d_in[8], F_, 32);
  make_map3(fn, &mp.out, d_out, 64, 8, S_, 64, 64, CU_TENSOR_MAP_SWIZZLE_128B);
  cudaFuncSetAttribute(fused_kernel, cudaFuncAttributeMaxDynamicSharedMemorySize, SMEM_BYTES);
  fused_kernel<<<128, 512, SMEM_BYTES, cudaStreamPerThread>>>(mp, (const uint16_t*)d_in[9], (const uint4*)d_in[2], (const uint4*)d_in[3], (const uint8_t*)d_in[8], (const uint8_t*)d_in[4]);
}
```

```cpp
#include <cuda_runtime.h>
#include <cuda_bf16.h>
#include <cuda.h>
#include <stdint.h>

#define DEG 2
#define REG_ATT 160
#define REG_GEMM 160
#define REG_PROD 32
#define FORCE_SLOW 0
#define NS_W 100
#define NS_KV 200
#define NS_F 200
#define NS_G 50
#define GW1 0
#define GW2 1
#define HINT 4000
#define EXP 0
#define POLLG 1
#define FK 2
#define GSL 1
#define QFIRST 1
#define WQCP 0

namespace {

constexpr int S_ = 2048, D_ = 512, F_ = 1792;
constexpr float QS = 0.25f * 1.4426950408889634f;

constexpr uint32_t sb = 1024;
constexpr uint32_t X_OFF = 0;
constexpr uint32_t W_OFF = 131072;
constexpr uint32_t KV_OFF = 196608;
constexpr uint32_t ONES_OFF = 229376;
constexpr uint32_t G_OFF = 229888;
constexpr uint32_t MISC_OFF = 231552;
constexpr uint32_t BAR_OFF = 231616;
constexpr uint32_t B_XFULL = BAR_OFF;
constexpr uint32_t B_PUB = B_XFULL + 64;
constexpr uint32_t B_GREADY = B_XFULL + 128;
constexpr uint32_t B_FFN1 = B_GREADY + 8;
constexpr uint32_t B_WFULL = B_FFN1 + 8;
constexpr uint32_t B_WEMPTY = B_WFULL + 32;
constexpr uint32_t B_KVFULL = B_WEMPTY + 32;
constexpr uint32_t B_KVEMPTY = B_KVFULL + 32;
constexpr uint32_t B_FFULL = B_KVEMPTY + 32;
constexpr uint32_t B_FEMPTY = B_FFULL + 64;
constexpr uint32_t B_WQ = B_FEMPTY + 64;
constexpr uint32_t SMEM_BYTES = B_WQ + 32;
constexpr uint32_t FST = 24576;
static_assert(SMEM_BYTES <= 232448, "smem");

constexpr int A_BYTES = 288 * 1024;
__device__ __align__(1024) uint8_t g_kv[32 * 4096];
__device__ uint4 g_kv0[16 * 512];
__device__ uint4 g_kvb[128 * 64];
__device__ __align__(1024) float2 g_gate[S_];
__device__ __align__(1024) uint8_t g_a[32 * A_BYTES];
__device__ __align__(256) uint32_t g_flags[64 + 32 * 64];
__device__ uint32_t g_done;

#define EV(i)
#define EVC(i)
struct Maps { CUtensorMap x, wq, wo, wg, wu, wd, out; };

__device__ __forceinline__ void wg_fence() { asm volatile("wgmma.fence.sync.aligned;" ::: "memory"); }
__device__ __forceinline__ void wg_commit() { asm volatile("wgmma.commit_group.sync.aligned;" ::: "memory"); }
template <int N> __device__ __forceinline__ void wg_wait() { asm volatile("wgmma.wait_group.sync.aligned %0;" ::"n"(N) : "memory"); }
template <int N> __device__ __forceinline__ void pin(float (&d)[N]) {
#pragma unroll
  for (int i = 0; i < N; i++) asm volatile("" : "+f"(d[i])::"memory");
}
template <int N> __device__ __forceinline__ void pinu(uint32_t (&d)[N]) {
#pragma unroll
  for (int i = 0; i < N; i++) asm volatile("" : "+r"(d[i])::"memory");
}
template <int N> __device__ __forceinline__ void zero(float (&d)[N]) {
#pragma unroll
  for (int i = 0; i < N; i++) d[i] = 0.f;
  pin(d);
}
__device__ __forceinline__ uint64_t mk64(uint32_t lo, uint32_t hi) { return ((uint64_t)hi << 32) | lo; }
__host__ __device__ constexpr uint32_t dhi(uint32_t sbo, uint32_t sw) { return (sbo >> 4) | (sw << 30); }
__device__ __forceinline__ uint32_t dlo(uint32_t addr, uint32_t lbo) { return (addr >> 4) | ((lbo >> 4) << 16); }

__device__ __forceinline__ void mbar_init(uint32_t b, uint32_t n) { asm volatile("mbarrier.init.shared::cta.b64 [%0], %1;" ::"r"(b), "r"(n) : "memory"); }
__device__ __forceinline__ void mbar_arrive(uint32_t b) { asm volatile("mbarrier.arrive.shared::cta.b64 _, [%0];" ::"r"(b) : "memory"); }
__device__ __forceinline__ void mbar_arrive2(uint32_t b) { asm volatile("mbarrier.arrive.shared::cta.b64 _, [%0], 2;" ::"r"(b) : "memory"); }
__device__ __forceinline__ void mbar_expect(uint32_t b, uint32_t bytes) { asm volatile("mbarrier.arrive.expect_tx.shared::cta.b64 _, [%0], %1;" ::"r"(b), "r"(bytes) : "memory"); }
__device__ __forceinline__ void mbar_wait(uint32_t b, uint32_t parity) {
  asm volatile(
      "{\n.reg .pred p;\n.reg .u32 c;\n"
      "mbarrier.try_wait.parity.shared::cta.b64 p, [%0], %1;\n"
      "@p bra DONE;\n"
      "mov.u32 c, 0;\n"
      "SPIN:\n"
      "mbarrier.try_wait.parity.shared::cta.b64 p, [%0], %1;\n"
      "@p bra DONE;\n"
      "add.u32 c, c, 1;\n"
      "setp.lt.u32 p, c, 0x100000;\n"
      "@p bra SPIN;\n"
      "trap;\n"
      "DONE:\n}\n" ::"r"(b), "r"(parity) : "memory");
}
template <int NS> __device__ __forceinline__ void mbar_wait_sleep(uint32_t b, uint32_t parity) {
  asm volatile(
      "{\n.reg .pred p;\n.reg .u32 c;\n"
      "mov.u32 c, 0;\n"
      "SPIN:\n"
      "mbarrier.try_wait.parity.shared::cta.b64 p, [%0], %1, %2;\n"
      "@p bra.uni DONE;\n"
      "add.u32 c, c, 1;\n"
      "setp.lt.u32 p, c, 0x40000;\n"
      "@p bra.uni SPIN;\n"
      "trap;\n"
      "DONE:\n}\n" ::"r"(b), "r"(parity), "n"(HINT) : "memory");
  return;
  asm volatile(
      "{\n.reg .pred p;\n.reg .u32 c;\n"
      "mov.u32 c, 0;\n"
      "SPIN:\n"
      "mbarrier.test_wait.parity.shared::cta.b64 p, [%0], %1;\n"
      "@p bra.uni DONE;\n"
      "nanosleep.u32 %2;\n"
      "add.u32 c, c, 1;\n"
      "setp.lt.u32 p, c, 0x100000;\n"
      "@p bra.uni SPIN;\n"
      "trap;\n"
      "DONE:\n}\n" ::"r"(b), "r"(parity), "n"(NS) : "memory");
}
#define ELECT "{\n.reg .pred p;\nelect.sync _|p, 0xffffffff;\n@p mbarrier.arrive.expect_tx.shared::cta.b64 _, [%0], %1;\n"
__device__ __forceinline__ void u_tma3d(uint32_t bar, uint32_t bytes, uint32_t dst, const CUtensorMap* m, int c0, int c1, int c2) {
  asm volatile(ELECT "@p cp.async.bulk.tensor.3d.shared::cluster.global.mbarrier::complete_tx::bytes [%2], [%3, {%4, %5, %6}], [%0];\n}\n" ::"r"(bar), "r"(bytes), "r"(dst), "l"(m), "r"(c0), "r"(c1), "r"(c2) : "memory");
}
__device__ __forceinline__ void u_tma4d(uint32_t bar, uint32_t bytes, uint32_t dst, const CUtensorMap* m, int c1, int c2, int c3) {
  asm volatile(ELECT "@p cp.async.bulk.tensor.4d.shared::cluster.global.mbarrier::complete_tx::bytes [%2], [%3, {0, %4, %5, %6}], [%0];\n}\n" ::"r"(bar), "r"(bytes), "r"(dst), "l"(m), "r"(c1), "r"(c2), "r"(c3) : "memory");
}
__device__ __forceinline__ void u_tma2d(uint32_t bar, uint32_t bytes, uint32_t dst, const CUtensorMap* m, int c0, int c1) {
  asm volatile(ELECT "@p cp.async.bulk.tensor.2d.shared::cluster.global.mbarrier::complete_tx::bytes [%2], [%3, {%4, %5}], [%0];\n}\n" ::"r"(bar), "r"(bytes), "r"(dst), "l"(m), "r"(c0), "r"(c1) : "memory");
}
__device__ __forceinline__ void u_tma2d_pair(uint32_t bar, uint32_t dst, const CUtensorMap* m0, const CUtensorMap* m1, int c0, int c1, int c1b) {
  asm volatile(ELECT "@p cp.async.bulk.tensor.2d.shared::cluster.global.mbarrier::complete_tx::bytes [%2], [%3, {%5, %6}], [%0];\n"
               "@p cp.async.bulk.tensor.2d.shared::cluster.global.mbarrier::complete_tx::bytes [%2 + 8192], [%4, {%5, %7}], [%0];\n}\n" ::"r"(bar), "r"(16384), "r"(dst), "l"(m0), "l"(m1), "r"(c0), "r"(c1), "r"(c1b) : "memory");
}
__device__ __forceinline__ void u_bulk(uint32_t bar, uint32_t bytes, uint32_t dst, const void* src) {
  asm volatile(ELECT "@p cp.async.bulk.shared::cluster.global.mbarrier::complete_tx::bytes [%2], [%3], %1, [%0];\n}\n" ::"r"(bar), "r"(bytes), "r"(dst), "l"(src) : "memory");
}
__device__ __forceinline__ void u_prefetch(const void* src, uint32_t bytes) {
  asm volatile("{\n.reg .pred p;\nelect.sync _|p, 0xffffffff;\n@p cp.async.bulk.prefetch.L2.global [%0], %1;\n}\n" ::"l"(src), "r"(bytes) : "memory");
}
__device__ __forceinline__ void fence_gpu() { asm volatile("fence.acq_rel.gpu;" ::: "memory"); }
__device__ __forceinline__ void st_rlx(uint32_t* p, uint32_t v) { asm volatile("st.relaxed.gpu.global.u32 [%0], %1;" ::"l"(p), "r"(v) : "memory"); }
__device__ __forceinline__ void st_rlx64(void* p, uint32_t a, uint32_t b) { asm volatile("st.relaxed.gpu.global.v2.u32 [%0], {%1, %2};" ::"l"(p), "r"(a), "r"(b) : "memory"); }
__device__ __forceinline__ void st_rlx128(void* p, uint32_t a, uint32_t b, uint32_t c, uint32_t d) { asm volatile("st.relaxed.gpu.global.v4.u32 [%0], {%1, %2, %3, %4};" ::"l"(p), "r"(a), "r"(b), "r"(c), "r"(d) : "memory"); }
__device__ __forceinline__ void ld_rlx128(uint32_t (&v)[4], const void* p, uint32_t c) {
  asm volatile("{\n.reg .pred p;\nsetp.ne.u32 p, %5, 0;\nmov.u32 %0, 0;\nmov.u32 %1, 0;\nmov.u32 %2, 0;\nmov.u32 %3, 0;\n@p ld.relaxed.gpu.global.v4.u32 {%0, %1, %2, %3}, [%4];\n}" : "=r"(v[0]), "=r"(v[1]), "=r"(v[2]), "=r"(v[3]) : "l"(p), "r"(c) : "memory");
}
__device__ __forceinline__ uint64_t ld_acq64(const uint32_t* p) { uint64_t v; asm volatile("ld.acquire.gpu.global.u64 %0, [%1];" : "=l"(v) : "l"(p) : "memory"); return v; }
__device__ __forceinline__ void tma2d(uint32_t dst, const CUtensorMap* m, int c0, int c1, uint32_t bar) {
  asm volatile("cp.async.bulk.tensor.2d.shared::cluster.global.mbarrier::complete_tx::bytes [%0], [%1, {%3, %4}], [%2];" ::"r"(dst), "l"(m), "r"(bar), "r"(c0), "r"(c1) : "memory");
}
__device__ __forceinline__ void bulk_ld(uint32_t dst, const void* src, uint32_t bytes, uint32_t bar) {
  asm volatile("cp.async.bulk.shared::cluster.global.mbarrier::complete_tx::bytes [%0], [%1], %2, [%3];" ::"r"(dst), "l"(src), "r"(bytes), "r"(bar) : "memory");
}
__device__ __forceinline__ void l2_prefetch(const void* src, uint32_t bytes) {
  asm volatile("cp.async.bulk.prefetch.L2.global [%0], %1;" ::"l"(src), "r"(bytes) : "memory");
}
__device__ __forceinline__ uint32_t ld_acq(const uint32_t* p) { uint32_t v; asm volatile("ld.acquire.gpu.global.u32 %0, [%1];" : "=r"(v) : "l"(p) : "memory"); return v; }
__device__ __forceinline__ void st_rel(uint32_t* p, uint32_t v) { asm volatile("st.release.gpu.global.u32 [%0], %1;" ::"l"(p), "r"(v) : "memory"); }
__device__ __forceinline__ void fence_async_all() { asm volatile("fence.proxy.async;" ::: "memory"); }
__device__ __forceinline__ void fence_async_gl() { asm volatile("fence.proxy.async.global;" ::: "memory"); }
__device__ __forceinline__ void bar_sync(int id) { asm volatile("bar.sync %0, 128;" ::"r"(id) : "memory"); }
__device__ __forceinline__ uint32_t pack2(float lo, float hi) { uint32_t r; asm("cvt.rn.bf16x2.f32 %0, %1, %2;" : "=r"(r) : "f"(hi), "f"(lo)); return r; }
__device__ __forceinline__ float ex2(float a) { float r; asm("ex2.approx.ftz.f32 %0, %1;" : "=f"(r) : "f"(a)); return r; }
__device__ __forceinline__ float sq4(float a, float b, float c, float d) { return fmaf(a, a, b * b) + fmaf(c, c, d * d); }
__device__ __forceinline__ void stg32(void* p, uint32_t v) { asm volatile("st.global.u32 [%0], %1;" ::"l"(p), "r"(v) : "memory"); }
__device__ __forceinline__ void stg64(void* p, uint32_t a, uint32_t b) { asm volatile("st.global.v2.u32 [%0], {%1, %2};" ::"l"(p), "r"(a), "r"(b) : "memory"); }
__device__ __forceinline__ void sts128(uint32_t a, uint32_t x, uint32_t y, uint32_t z, uint32_t w) { asm volatile("st.shared.v4.u32 [%0], {%1, %2, %3, %4};" ::"r"(a), "r"(x), "r"(y), "r"(z), "r"(w) : "memory"); }
__device__ __forceinline__ void stsm4(uint32_t a, uint32_t x, uint32_t y, uint32_t z, uint32_t w) { asm volatile("stmatrix.sync.aligned.m8n8.x4.shared.b16 [%0], {%1,%2,%3,%4};" ::"r"(a), "r"(x), "r"(y), "r"(z), "r"(w) : "memory"); }
__device__ __forceinline__ void sts64(uint32_t a, uint32_t x, uint32_t y) { asm volatile("st.shared.v2.u32 [%0], {%1, %2};" ::"r"(a), "r"(x), "r"(y) : "memory"); }
__device__ __forceinline__ void sts32(uint32_t a, uint32_t v) { asm volatile("st.shared.u32 [%0], %1;" ::"r"(a), "r"(v) : "memory"); }
__device__ __forceinline__ uint32_t lds32(uint32_t a) { uint32_t v; asm volatile("ld.shared.u32 %0, [%1];" : "=r"(v) : "r"(a) : "memory"); return v; }

__device__ __forceinline__ void mma_qk(uint32_t (&d)[16], const uint32_t (&a)[4], uint64_t b) {
  asm volatile("{\n.reg .pred p;\nsetp.ne.b32 p, 0, 0;\n"
    "wgmma.mma_async.sync.aligned.m64n64k16.f16.f16.f16 {%0,%1,%2,%3,%4,%5,%6,%7,%8,%9,%10,%11,%12,%13,%14,%15}, {%16,%17,%18,%19}, %20, p, 1, 1, 0;\n}\n"
    : "+r"(d[0]),"+r"(d[1]),"+r"(d[2]),"+r"(d[3]),"+r"(d[4]),"+r"(d[5]),"+r"(d[6]),"+r"(d[7]),"+r"(d[8]),"+r"(d[9]),"+r"(d[10]),"+r"(d[11]),"+r"(d[12]),"+r"(d[13]),"+r"(d[14]),"+r"(d[15]) : "r"(a[0]),"r"(a[1]),"r"(a[2]),"r"(a[3]),"l"(b));
}
__device__ __forceinline__ void mma_pv(uint32_t (&d)[6], const uint32_t (&a)[4], uint64_t b) {
  asm volatile("{\n.reg .pred p;\nsetp.ne.b32 p, 1, 0;\n"
    "wgmma.mma_async.sync.aligned.m64n24k16.f16.f16.f16 {%0,%1,%2,%3,%4,%5}, {%6,%7,%8,%9}, %10, p, 1, 1, 1;\n}\n"
    : "+r"(d[0]),"+r"(d[1]),"+r"(d[2]),"+r"(d[3]),"+r"(d[4]),"+r"(d[5]) : "r"(a[0]),"r"(a[1]),"r"(a[2]),"r"(a[3]),"l"(b));
}
__device__ __forceinline__ void mma_pv0(uint32_t (&d)[6], const uint32_t (&a)[4], uint64_t b) {
  asm volatile("{\n.reg .pred p;\nsetp.ne.b32 p, 0, 0;\n"
    "wgmma.mma_async.sync.aligned.m64n24k16.f16.f16.f16 {%0,%1,%2,%3,%4,%5}, {%6,%7,%8,%9}, %10, p, 1, 1, 1;\n}\n"
    : "+r"(d[0]),"+r"(d[1]),"+r"(d[2]),"+r"(d[3]),"+r"(d[4]),"+r"(d[5]) : "r"(a[0]),"r"(a[1]),"r"(a[2]),"r"(a[3]),"l"(b));
}
__device__ __forceinline__ void mma_ss_t128(float (&d)[64], uint64_t a, uint64_t b, int acc) {
  asm volatile("{\n.reg .pred p;\nsetp.ne.b32 p, %66, 0;\n"
    "wgmma.mma_async.sync.aligned.m64n128k16.f32.bf16.bf16 {%0,%1,%2,%3,%4,%5,%6,%7,%8,%9,%10,%11,%12,%13,%14,%15,%16,%17,%18,%19,%20,%21,%22,%23,%24,%25,%26,%27,%28,%29,%30,%31,%32,%33,%34,%35,%36,%37,%38,%39,%40,%41,%42,%43,%44,%45,%46,%47,%48,%49,%50,%51,%52,%53,%54,%55,%56,%57,%58,%59,%60,%61,%62,%63}, %64, %65, p, 1, 1, 0, 1;\n}\n"
    : "+f"(d[0]),"+f"(d[1]),"+f"(d[2]),"+f"(d[3]),"+f"(d[4]),"+f"(d[5]),"+f"(d[6]),"+f"(d[7]),"+f"(d[8]),"+f"(d[9]),"+f"(d[10]),"+f"(d[11]),"+f"(d[12]),"+f"(d[13]),"+f"(d[14]),"+f"(d[15]),"+f"(d[16]),"+f"(d[17]),"+f"(d[18]),"+f"(d[19]),"+f"(d[20]),"+f"(d[21]),"+f"(d[22]),"+f"(d[23]),"+f"(d[24]),"+f"(d[25]),"+f"(d[26]),"+f"(d[27]),"+f"(d[28]),"+f"(d[29]),"+f"(d[30]),"+f"(d[31]),"+f"(d[32]),"+f"(d[33]),"+f"(d[34]),"+f"(d[35]),"+f"(d[36]),"+f"(d[37]),"+f"(d[38]),"+f"(d[39]),"+f"(d[40]),"+f"(d[41]),"+f"(d[42]),"+f"(d[43]),"+f"(d[44]),"+f"(d[45]),"+f"(d[46]),"+f"(d[47]),"+f"(d[48]),"+f"(d[49]),"+f"(d[50]),"+f"(d[51]),"+f"(d[52]),"+f"(d[53]),"+f"(d[54]),"+f"(d[55]),"+f"(d[56]),"+f"(d[57]),"+f"(d[58]),"+f"(d[59]),"+f"(d[60]),"+f"(d[61]),"+f"(d[62]),"+f"(d[63]) : "l"(a),"l"(b),"r"(acc));
}
__device__ __forceinline__ void mma_ss_t64(float (&d)[32], uint64_t a, uint64_t b, int acc) {
  asm volatile("{\n.reg .pred p;\nsetp.ne.b32 p, %34, 0;\n"
    "wgmma.mma_async.sync.aligned.m64n64k16.f32.bf16.bf16 {%0,%1,%2,%3,%4,%5,%6,%7,%8,%9,%10,%11,%12,%13,%14,%15,%16,%17,%18,%19,%20,%21,%22,%23,%24,%25,%26,%27,%28,%29,%30,%31}, %32, %33, p, 1, 1, 0, 1;\n}\n"
    : "+f"(d[0]),"+f"(d[1]),"+f"(d[2]),"+f"(d[3]),"+f"(d[4]),"+f"(d[5]),"+f"(d[6]),"+f"(d[7]),"+f"(d[8]),"+f"(d[9]),"+f"(d[10]),"+f"(d[11]),"+f"(d[12]),"+f"(d[13]),"+f"(d[14]),"+f"(d[15]),"+f"(d[16]),"+f"(d[17]),"+f"(d[18]),"+f"(d[19]),"+f"(d[20]),"+f"(d[21]),"+f"(d[22]),"+f"(d[23]),"+f"(d[24]),"+f"(d[25]),"+f"(d[26]),"+f"(d[27]),"+f"(d[28]),"+f"(d[29]),"+f"(d[30]),"+f"(d[31]) : "l"(a),"l"(b),"r"(acc));
}
__device__ __forceinline__ void mma_ss_t24(float (&d)[12], uint64_t a, uint64_t b, int acc) {
  asm volatile("{\n.reg .pred p;\nsetp.ne.b32 p, %14, 0;\n"
    "wgmma.mma_async.sync.aligned.m64n24k16.f32.bf16.bf16 {%0,%1,%2,%3,%4,%5,%6,%7,%8,%9,%10,%11}, %12, %13, p, 1, 1, 0, 1;\n}\n"
    : "+f"(d[0]),"+f"(d[1]),"+f"(d[2]),"+f"(d[3]),"+f"(d[4]),"+f"(d[5]),"+f"(d[6]),"+f"(d[7]),"+f"(d[8]),"+f"(d[9]),"+f"(d[10]),"+f"(d[11]) : "l"(a),"l"(b),"r"(acc));
}

__device__ __forceinline__ uint32_t hfma2(uint32_t a, uint32_t b, uint32_t c) { uint32_t r; asm("fma.rn.f16x2 %0, %1, %2, %3;" : "=r"(r) : "r"(a), "r"(b), "r"(c)); return r; }
__device__ __forceinline__ uint32_t packh(float lo, float hi) { uint32_t r; asm("cvt.rn.f16x2.f32 %0, %1, %2;" : "=r"(r) : "f"(hi), "f"(lo)); return r; }
__device__ __forceinline__ void unpackh(uint32_t a, float& lo, float& hi) { asm("{\n.reg .b16 l, h;\nmov.b32 {l, h}, %2;\ncvt.f32.f16 %0, l;\ncvt.f32.f16 %1, h;\n}" : "=f"(lo), "=f"(hi) : "r"(a)); }
__device__ __forceinline__ uint32_t exp2_mufu(uint32_t s) { uint32_t r; asm("ex2.approx.f16x2 %0, %1;" : "=r"(r) : "r"(s)); return r; }
__device__ __forceinline__ uint32_t exp2_fma(uint32_t s) {
  uint32_t t, u;
  asm("fma.rn.relu.f16x2 %0, %1, %2, %3;" : "=r"(t) : "r"(s), "r"(0x02000200u), "r"(0x000a000au));
  asm("mul.rn.f16x2 %0, %1, %2;" : "=r"(u) : "r"(s), "r"(0x02000200u));
  const uint32_t f = hfma2(u, 0xF800F800u, s);
  const uint32_t y = hfma2(hfma2(f, 0x45614561u, 0x27f627f6u), f, 0x05aa05aau);
  return y + (t << 10);
}
template <int J> __device__ __forceinline__ void sm_unit(const uint32_t (&s)[16], uint32_t (&p)[4]) {
  p[0] = exp2_mufu(s[4 * J]); p[1] = exp2_fma(s[4 * J + 1]); p[2] = exp2_mufu(s[4 * J + 2]); p[3] = exp2_fma(s[4 * J + 3]);
}

#define KD(lo) mk64((lo), dhi(256, 3))
#define VO(x) ((uint32_t)(x) - ((uint32_t)(x) << 16))

__device__ __forceinline__ void flush(uint32_t (&a)[6], uint32_t (&o)[6]) {
#pragma unroll
  for (int i = 0; i < 6; i++) asm volatile("add.rn.f16x2 %0, %0, %1;" : "+r"(a[i]) : "r"(o[i]) : "memory");
}
__device__ __forceinline__ void attn_fast(const uint32_t (&q0)[4], const uint32_t (&q1)[4], uint32_t (&a0)[6], uint32_t (&a1)[6], int lane) {
  const uint32_t kvfull = sb + B_KVFULL, kvempty = sb + B_KVEMPTY;
  const uint32_t kbase = dlo(sb + KV_OFF, 16), vbase = dlo(sb + KV_OFF, ONES_OFF - KV_OFF);
  uint32_t s0[16] = {}, s1[16] = {}, o0[6] = {}, o1[6] = {};
  pinu(s0); pinu(s1); pinu(o0); pinu(o1);
  {
    uint32_t p0[4]={0,0,0,0}; pinu(p0);
    uint32_t p1[4]={0,0,0,0}; pinu(p1);
    uint32_t p2[4]={0,0,0,0}; pinu(p2);
    uint32_t p3[4]={0,0,0,0}; pinu(p3);
    wg_fence(); mma_qk(s0, q0, KD(kbase)); wg_commit(); wg_wait<0>(); pinu(s0);
    uint32_t vprev = vbase - VO(512);
#pragma unroll 1
    for (int it = 0; it < 8; it++) {
      const uint32_t sA = (it & 1) * 2, ph = (it >> 1) & 1, phn = ((it + 1) >> 1) & 1;
      const uint32_t kcur = kbase + sA * 512, knxt = kbase + (sA ^ 2) * 512, vcur = vbase + VO(sA * 512);
      wg_fence();
      mma_qk(s1,q1,KD(kcur+0));
      mma_pv0(o1,p2,KD(vprev+VO(960)));
      mma_pv(o1,p3,KD(vprev+VO(992)));
      wg_commit();
      flush(a0, o0);
      sm_unit<0>(s0,p0);
      sm_unit<1>(s0,p1);
      wg_fence();
      mma_pv0(o0,p0,KD(vcur+VO(128)));
      mma_pv(o0,p1,KD(vcur+VO(160)));
      wg_commit();
      wg_wait<1>();
      if (!(EXP & 32) && lane==0 && it!=0) mbar_arrive(kvempty+8*((sA^2)+1));
      sm_unit<2>(s0,p2);
      sm_unit<3>(s0,p3);
      wg_fence();
      mma_qk(s0,q0,KD(kcur+256));
      mma_pv(o0,p2,KD(vcur+VO(192)));
      mma_pv(o0,p3,KD(vcur+VO(224)));
      wg_commit();
      wg_wait<1>(); pinu(s1);
      sm_unit<0>(s1,p0);
      sm_unit<1>(s1,p1);
      wg_fence();
      mma_pv(o1,p0,KD(vcur+VO(128)));
      mma_pv(o1,p1,KD(vcur+VO(160)));
      wg_commit();
      wg_wait<1>();
      sm_unit<2>(s1,p2);
      sm_unit<3>(s1,p3);
      wg_fence();
      mma_qk(s1,q1,KD(kcur+256));
      mma_pv(o1,p2,KD(vcur+VO(192)));
      mma_pv(o1,p3,KD(vcur+VO(224)));
      wg_commit();
      wg_wait<1>(); pinu(s0);
      sm_unit<0>(s0,p0);
      sm_unit<1>(s0,p1);
      wg_fence();
      mma_pv(o0,p0,KD(vcur+VO(384)));
      mma_pv(o0,p1,KD(vcur+VO(416)));
      wg_commit();
      wg_wait<1>();
      sm_unit<2>(s0,p2);
      sm_unit<3>(s0,p3);
      if (!(EXP & 16)) mbar_wait(kvfull+8*(sA+1), ph);
      wg_fence();
      mma_qk(s0,q0,KD(kcur+512));
      mma_pv(o0,p2,KD(vcur+VO(448)));
      mma_pv(o0,p3,KD(vcur+VO(480)));
      wg_commit();
      wg_wait<1>(); pinu(s1);
      sm_unit<0>(s1,p0);
      sm_unit<1>(s1,p1);
      wg_fence();
      mma_pv(o1,p0,KD(vcur+VO(384)));
      mma_pv(o1,p1,KD(vcur+VO(416)));
      wg_commit();
      wg_wait<1>();
      sm_unit<2>(s1,p2);
      sm_unit<3>(s1,p3);
      wg_fence();
      mma_qk(s1,q1,KD(kcur+512));
      mma_pv(o1,p2,KD(vcur+VO(448)));
      mma_pv(o1,p3,KD(vcur+VO(480)));
      wg_commit();
      wg_wait<1>(); pinu(s0);
      sm_unit<0>(s0,p0);
      sm_unit<1>(s0,p1);
      wg_fence();
      mma_pv(o0,p0,KD(vcur+VO(640)));
      mma_pv(o0,p1,KD(vcur+VO(672)));
      wg_commit();
      wg_wait<1>();
      if (!(EXP & 32) && lane==0) mbar_arrive(kvempty+8*sA);
      sm_unit<2>(s0,p2);
      sm_unit<3>(s0,p3);
      wg_fence();
      mma_qk(s0,q0,KD(kcur+768));
      mma_pv(o0,p2,KD(vcur+VO(704)));
      mma_pv(o0,p3,KD(vcur+VO(736)));
      wg_commit();
      wg_wait<1>(); pinu(s1);
      sm_unit<0>(s1,p0);
      sm_unit<1>(s1,p1);
      wg_fence();
      mma_pv(o1,p0,KD(vcur+VO(640)));
      mma_pv(o1,p1,KD(vcur+VO(672)));
      wg_commit();
      wg_wait<1>();
      sm_unit<2>(s1,p2);
      sm_unit<3>(s1,p3);
      wg_fence();
      mma_qk(s1,q1,KD(kcur+768));
      mma_pv(o1,p2,KD(vcur+VO(704)));
      mma_pv(o1,p3,KD(vcur+VO(736)));
      wg_commit();
      wg_wait<1>(); pinu(s0);
      sm_unit<0>(s0,p0);
      sm_unit<1>(s0,p1);
      wg_fence();
      mma_pv(o0,p0,KD(vcur+VO(896)));
      mma_pv(o0,p1,KD(vcur+VO(928)));
      wg_commit();
      wg_wait<1>();
      sm_unit<2>(s0,p2);
      sm_unit<3>(s0,p3);
      if (!(EXP & 16)) mbar_wait(kvfull+8*(sA^2), phn);
      wg_fence();
      mma_qk(s0,q0,KD(knxt));
      mma_pv(o0,p2,KD(vcur+VO(960)));
      mma_pv(o0,p3,KD(vcur+VO(992)));
      wg_commit();
      wg_wait<1>(); pinu(s1);
      sm_unit<0>(s1,p0);
      sm_unit<1>(s1,p1);
      wg_fence();
      mma_pv(o1,p0,KD(vcur+VO(896)));
      mma_pv(o1,p1,KD(vcur+VO(928)));
      wg_commit();
      wg_wait<1>();
      sm_unit<2>(s1,p2);
      sm_unit<3>(s1,p3);
      wg_wait<0>(); pinu(s0); pinu(o0); pinu(o1);
      flush(a1, o1);
      vprev = vcur;
    }
    wg_fence();
    mma_pv0(o1,p2,KD(vprev+VO(960)));
    mma_pv(o1,p3,KD(vprev+VO(992)));
    wg_commit(); flush(a0, o0); wg_wait<0>(); pinu(o1);
    if (lane == 0) mbar_arrive(kvempty + 8 * 3);
    flush(a1, o1);
  }
}

__device__ __forceinline__ void mma16816(float* d, const uint32_t (&a)[4], uint32_t b0, uint32_t b1) {
  asm("mma.sync.aligned.m16n8k16.row.col.f32.bf16.bf16.f32 {%0,%1,%2,%3}, {%4,%5,%6,%7}, {%8,%9}, {%0,%1,%2,%3};"
      : "+f"(d[0]), "+f"(d[1]), "+f"(d[2]), "+f"(d[3]) : "r"(a[0]), "r"(a[1]), "r"(a[2]), "r"(a[3]), "r"(b0), "r"(b1));
}
__device__ __forceinline__ uint32_t trans8(uint32_t a) { uint32_t r; asm("movmatrix.sync.aligned.m8n8.trans.b16 %0, %1;" : "=r"(r) : "r"(a)); return r; }
__device__ __forceinline__ void attn_online(const uint32_t (&qn)[4], float g0, float g1, uint8_t* dst, int pass, int lane) {
  uint32_t q[4];
#pragma unroll
  for (int i = 0; i < 4; i++) {
    const int src = (lane & ~3) | ((2 * lane + (i >> 1)) & 3);
    const uint32_t u = __shfl_sync(~0u, qn[i & 1], src), v = __shfl_sync(~0u, qn[2 + (i & 1)], src);
    q[i] = (lane & 2) ? v : u;
  }
  float o[12] = {};
  float m0 = -3e38f, m1 = -3e38f;
#pragma unroll 2
  for (int b = 0; b < 128; b++) {
    const uint4 k = __ldcg(g_kvb + b * 64 + lane), v = __ldcg(g_kvb + b * 64 + 32 + lane);
    float s[8] = {};
    mma16816(s, q, k.x, k.z); mma16816(s + 4, q, k.y, k.w);
    float x = fmaxf(fmaxf(m0, fmaxf(s[0], s[1])), fmaxf(s[4], s[5])), y = fmaxf(fmaxf(m1, fmaxf(s[2], s[3])), fmaxf(s[6], s[7]));
    x = fmaxf(x, __shfl_xor_sync(~0u, x, 1)); x = fmaxf(x, __shfl_xor_sync(~0u, x, 2));
    y = fmaxf(y, __shfl_xor_sync(~0u, y, 1)); y = fmaxf(y, __shfl_xor_sync(~0u, y, 2));
    const float cx = ex2((m0 - x) * QS), cy = ex2((m1 - y) * QS);
    m0 = x; m1 = y;
#pragma unroll
    for (int j = 0; j < 3; j++) { o[4 * j] *= cx; o[4 * j + 1] *= cx; o[4 * j + 2] *= cy; o[4 * j + 3] *= cy; }
    const uint32_t p[4] = {pack2(ex2((s[0] - x) * QS), ex2((s[1] - x) * QS)), pack2(ex2((s[2] - y) * QS), ex2((s[3] - y) * QS)),
                           pack2(ex2((s[4] - x) * QS), ex2((s[5] - x) * QS)), pack2(ex2((s[6] - y) * QS), ex2((s[7] - y) * QS))};
    mma16816(o, p, trans8(v.x), trans8(v.y)); mma16816(o + 4, p, trans8(v.z), trans8(v.w)); mma16816(o + 8, p, 0x3F803F80u, 0x3F803F80u);
  }
  const float a = __fdividef(g0, o[8]), b = __fdividef(g1, o[10]);
  const uint32_t w0 = pack2(o[0] * a, o[1] * a), w1 = pack2(o[2] * b, o[3] * b), w2 = pack2(o[4] * a, o[5] * a), w3 = pack2(o[6] * b, o[7] * b);
  if (pass == 0) {
    dst += (lane & 2) * 508 + (lane & 1) * 4;
    stg64(dst, w0, w2); stg64(dst + 128, w1, w3);
  } else {
    dst += (lane & 1) * 16 - (lane & 2) * 12;
    st_rlx64(dst, ~w0, ~w1); st_rlx64(dst + 16, ~w2, ~w3);
  }
}

__device__ __forceinline__ void store_o(const float (&o)[12], float g0, float g1, uint8_t* dst, int pass) {
  const float a = __fdividef(g0, o[8]), b = __fdividef(g1, o[10]);
  const uint32_t w0 = pack2(o[0] * a, o[1] * a), w1 = pack2(o[2] * b, o[3] * b), w2 = pack2(o[4] * a, o[5] * a), w3 = pack2(o[6] * b, o[7] * b);
  if (pass == 0) { stg32(dst, w0); stg32(dst + 128, w1); stg32(dst + 1024, w2); stg32(dst + 1152, w3); }
  else st_rlx128(dst, ~w0, ~w1, ~w2, ~w3);
}

__device__ __forceinline__ void attn_passes(uint32_t (&qh)[4][4], uint32_t (&qb)[4][4], float qn, uint8_t* odst, int wg) {
  const int lane = threadIdx.x & 31;
  float g0 = 0.f, g1 = 0.f;
#pragma unroll 1
  for (int p = 0; p < 2; p++) {
    {
      uint32_t a0[6] = {}, a1[6] = {};
      attn_fast(qh[0], qh[1], a0, a1, lane);
      if (p == 0) {
        mbar_wait(sb + B_GREADY, 0);
        const uint32_t ga = sb + G_OFF + ((threadIdx.x >> 5) * 16 + (lane >> 2)) * 8;
        g0 = __uint_as_float(lds32(ga)); g1 = __uint_as_float(lds32(ga + 64));
        const float kn = __uint_as_float(lds32(sb + MISC_OFF + 32));
        qn = !FORCE_SLOW && qn * kn <= 372.f && qn <= 65536.f && kn <= 65536.f ? 128.f : NAN;
      }
      float o0[12], o1[12], hi = 0.f;
#pragma unroll
      for (int i = 0; i < 6; i++) { unpackh(a0[i], o0[2 * i], o0[2 * i + 1]); unpackh(a1[i], o1[2 * i], o1[2 * i + 1]); }
      const float lo = fminf(fminf(o0[8], o0[10]), fminf(o1[8], o1[10]));
#pragma unroll
      for (int i = 0; i < 11; i++) hi += fabsf(o0[i]) + fabsf(o1[i]);
      const bool ok = lo >= qn && hi < INFINITY;
      if (__all_sync(~0u, ok)) {
        store_o(o0, g0, g1, odst, p);
        store_o(o1, g0, g1, odst + 2048, p);
      } else {
#pragma unroll 1
        for (int h = 0; h < 2; h++) {
          attn_online(qb[0], g0, g1, odst + h * 2048, p, lane);
#pragma unroll
          for (int i = 0; i < 4; i++) qb[0][i] = qb[1][i];
        }
      }
    }
    if (p == 0) {
      odst += 32768 + (threadIdx.x & 96) * 8 + lane * 12;
      st_rlx128(odst, 0, 0, 0, 0); st_rlx128(odst + 2048, 0, 0, 0, 0);
      __syncwarp();
      if (lane == 0) mbar_arrive(sb + B_PUB + 32);
    }
#pragma unroll
    for (int i = 0; i < 4; i++) { qh[0][i] = qh[2][i]; qh[1][i] = qh[3][i]; qb[0][i] = qb[2][i]; qb[1][i] = qb[3][i]; }
  }
}

__device__ __forceinline__ float geglu(float x, float u, float c) {
  const float y = x * fmaf(x * x, 0.044715f * 0.7978845608028654f, 0.7978845608028654f);
  float t; asm("tanh.approx.f32 %0, %1;" : "=f"(t) : "f"(y));
  const float h = x * u * c;
  return fmaf(h, t, h);
}
__device__ __forceinline__ void store_h(const float (&d)[64], float c0, float c1, uint8_t* dst) {
#pragma unroll
  for (int j = 0; j < 8; j++) {
    stg32(dst + j * 1024, pack2(geglu(d[4 * j], d[32 + 4 * j], c0), geglu(d[4 * j + 1], d[33 + 4 * j], c0)));
    stg32(dst + j * 1024 + 128, pack2(geglu(d[4 * j + 2], d[34 + 4 * j], c1), geglu(d[4 * j + 3], d[35 + 4 * j], c1)));
  }
}

__global__ void __launch_bounds__(512, 1)
fused_kernel(const __grid_constant__ Maps mp, const uint16_t* __restrict__ gate_w, const uint4* __restrict__ wk, const uint4* __restrict__ wv,
             const uint8_t* __restrict__ wd_raw, const uint8_t* __restrict__ wo_raw, const uint8_t* __restrict__ wq_raw) {
  extern __shared__ __align__(1024) uint8_t smem[];
  const int tid = threadIdx.x, lane = tid & 31;
  const int warp = __shfl_sync(~0u, tid >> 5, 0);
  const int wg = warp >> 2, wq4 = warp & 3;
  const int tb = blockIdx.x >> 3, cg = blockIdx.x & 7;
  const int half = cg & 1;

  if (warp == 12) {
    if (lane == 0) {
      EV(0);
      if ((uint32_t)__cvta_generic_to_shared(smem) != sb) __trap();
      for (int i = 0; i < 8; i++) mbar_init(sb + B_XFULL + 8 * i, 1);
      for (int i = 0; i < 4; i++) mbar_init(sb + B_WQ + 8 * i, 1);
      asm volatile("fence.mbarrier_init.release.cluster;" ::: "memory");
    }
    __syncwarp();
    const uint32_t xb = sb + B_XFULL + 32 * half, xd = sb + X_OFF + half * 65536;
    const int row = tb * 128 + half * 64;
    if (cg < 4) {
#pragma unroll
      for (int j = 0; j < 4; j++) u_tma3d(xb + 8 * j, 16384, xd + j * 16384, &mp.x, 0, row, 2 * j);
    }
#pragma unroll
    for (int j = 0; j < 4; j++) {
      if (!WQCP) u_tma2d(sb + B_WQ + 8 * j, 16384, sb + W_OFF + j * 16384, &mp.wq, cg * 64, j * 128);
      u_tma3d((xb ^ 32) + 8 * j, 16384, (xd ^ 65536) + j * 16384, &mp.x, 0, row ^ 64, 2 * j);
      if (cg >= 4) u_tma3d(xb + 8 * j, 16384, xd + j * 16384, &mp.x, 0, row, 2 * j);
    }
  } else if (tid == 416) {
    mbar_init(sb + B_GREADY, 1); mbar_init(sb + B_FFN1, 4);
    for (int i = 0; i < 4; i++) { mbar_init(sb + B_WFULL + 8 * i, 1); mbar_init(sb + B_WEMPTY + 8 * i, 8); mbar_init(sb + B_KVFULL + 8 * i, 1); mbar_init(sb + B_KVEMPTY + 8 * i, 8); mbar_init(sb + B_PUB + 8 * i, 4); }
    mbar_init(sb + B_PUB + 32, 8);
    for (int i = 0; i < 8; i++) { mbar_init(sb + B_FFULL + 8 * i, 2); mbar_init(sb + B_FEMPTY + 8 * i, 4); }
    asm volatile("fence.mbarrier_init.release.cluster;" ::: "memory");
  } else if (tid == 448) {
    asm volatile("prefetch.tensormap [%0];" ::"l"(&mp.wg) : "memory");
    asm volatile("prefetch.tensormap [%0];" ::"l"(&mp.wu) : "memory");
    asm volatile("prefetch.tensormap [%0];" ::"l"(&mp.wd) : "memory");
    asm volatile("prefetch.tensormap [%0];" ::"l"(&mp.wo) : "memory");
    asm volatile("prefetch.tensormap [%0];" ::"l"(&mp.out) : "memory");
  }
  uint4 wa[4], wb[4];
  uint32_t wz[4];
  if (cg < 4 && wg == 2) {
    const uint4* w = (cg < 2 ? wk : wv) + (tid & 127) * 2;
#pragma unroll
    for (int i = 0; i < 4; i++) { wa[i] = __ldg(w + i * 256); wb[i] = __ldg(w + i * 256 + 1); wz[i] = __ldg(gate_w + (tid & 127) + i * 128); }
  }
  if (WQCP && wg < 2) {
    const uint8_t* src = wq_raw + (tid >> 3) * 1024 + cg * 128 + (tid & 7) * 16;
    const uint32_t dst = sb + W_OFF + (tid >> 3) * 128 + (((tid ^ (tid >> 3)) & 7) << 4);
#pragma unroll
    for (int i = 0; i < 16; i++) {
      asm volatile("cp.async.cg.shared.global [%0], [%1], 16;" ::"r"(dst + i * 4096), "l"(src + i * 32768) : "memory");
      if ((i & 3) == 3) asm volatile("cp.async.commit_group;" ::: "memory");
    }
  }
  if (tid < 128) { sts32(sb + ONES_OFF + tid * 4, 0x3C003C00u); asm volatile("fence.proxy.async.shared::cta;" ::: "memory"); }
  __syncthreads();
  if (tid == 0) EV(1);

  uint8_t* const a_tb = g_a + (size_t)(tb * 2) * A_BYTES;
  uint32_t* const fl_tb = g_flags + 64 + tb * 128;

  if (wg == 3) {
    asm volatile("setmaxnreg.dec.sync.aligned.u32 %0;" ::"n"(REG_PROD));
    if (wq4 == 0) {
#pragma unroll 1
      for (int n = 0; n < 32; n++) {
        const int s = n & 3;
        const int hc = n < 24 ? (n & 24) + cg : 24 + (cg >> 1);
        mbar_wait_sleep<NS_W>(sb + B_WEMPTY + 8 * s, (n >> 2) & 1);
        u_tma2d_pair(sb + B_WFULL + 8 * s, sb + W_OFF + s * 16384, &mp.wg, &mp.wu, hc * 64, (n & 7) * 64, (n & 7) * 64);
        if (n == 8) { u_prefetch(wd_raw + blockIdx.x * 14336, 14336); u_prefetch(wo_raw + blockIdx.x * 4096, 4096); }
      }
      mbar_wait_sleep<NS_W>(sb + B_FFN1, 0);
#pragma unroll 1
      for (int n = 0; n < 36; n++) {
        const int s = n & 7;
        mbar_wait_sleep<NS_W>(sb + B_FEMPTY + 8 * s, ((n >> 3) & 1) ^ 1);
        u_tma4d(sb + B_FFULL + 8 * s, 16384, sb + s * FST + 8192, n < 28 ? &mp.wd : &mp.wo, n & 32, n < 28 ? 2 * n : 2 * (n & 3), cg & 6);
        if (n >= 32 && lane == 0) mbar_arrive(sb + B_FFULL + 8 * s);
      }
    } else if (wq4 == 1) {
      if (cg < 4) asm volatile("bar.sync 4, 192;" ::: "memory");
      uint32_t todo = 0x55555555u ^ (1u << 2 * tb), rdy = 0;
#pragma unroll 1
      for (int n = 1; n < 33; n++) {
        if (n == 15 ? rdy != 0x55555555u : !(rdy & todo)) {
          for (int i = 0; n == 15 ? rdy != 0x55555555u : !(rdy & todo); i++) {
            const uint64_t f = ld_acq64(g_flags + 2 * lane);
            rdy = __ballot_sync(~0u, (uint32_t)f & (uint32_t)(f >> 32) & 1);
            rdy &= (rdy >> 1) & 0x55555555u;
            if (i > 0x100000) __trap();
          }
          fence_async_gl();
        }
        const int c = __ffs(rdy & todo) - 1, s = n & 3;
        todo ^= 1u << c;
        if (!todo) todo = 0x55555555u;
        mbar_wait_sleep<NS_KV>(sb + B_KVEMPTY + 8 * s, ((n >> 2) & 1) ^ 1);
        u_bulk(sb + B_KVFULL + 8 * s, 8192, sb + KV_OFF + s * 8192, g_kv + c * 4096);
      }
    } else if (wq4 == 3) {
      if (cg < 4) {
        uint32_t* const fl = g_flags + (tb * 2 + half) * 2 + (cg >> 1);
        asm volatile("bar.sync 4, 192;" ::: "memory");
        fence_gpu();
        if (lane == 0) { st_rlx(fl, 1); EV(2); }
        asm volatile("bar.sync 5, 160;" ::: "memory");
        const uint32_t m = __reduce_max_sync(~0u, lds32(sb + MISC_OFF + 48 + (lane & 3) * 4));
        fence_gpu();
        if (lane == 0) st_rlx(fl, m | 3);
      }
#pragma unroll 1
      for (int e = 0; e < 5; e++) {
        mbar_wait_sleep<NS_W>(sb + B_PUB + 8 * e, 0);
        fence_gpu();
        const int idx = e < 3 ? 2 * (e * 8 + cg) : e == 3 ? 2 * (24 + (cg >> 1)) : 2 * cg + 1;
        if (lane < 2 && (e != 3 || lane == half)) st_rlx(fl_tb + lane * 64 + idx, 1);
      }
    } else {
      {
        mbar_wait_sleep<NS_W>(sb + B_KVEMPTY + 8 * GSL, 0);
        uint64_t f;
        for (int i = 0;; i++) {
          f = ld_acq64(g_flags + 2 * lane);
          if (__all_sync(~0u, (uint32_t)f & (uint32_t)(f >> 32) & 2)) break;
          if (i > 0x100000) __trap();
          __nanosleep(NS_F);
        }
        fence_async_gl();
        const uint32_t fk = __reduce_max_sync(~0u, max((uint32_t)f, (uint32_t)(f >> 32)));
        if (lane == 0) sts32(sb + MISC_OFF + 32, fk);
        __syncwarp();
        u_bulk(sb + B_GREADY, 1024, sb + G_OFF, g_gate + tb * 128);
      }
      mbar_wait_sleep<NS_W>(sb + B_FFN1, 0);
      const uint32_t* fl = fl_tb + half * 64 + 2 * lane;
      const uint8_t* src = a_tb + half * A_BYTES;
      int ready = 0;
#pragma unroll 1
      for (int n = 0; n < 32; n++) {
        if (n >= ready) {
          for (int i = 0;; i++) {
            const uint64_t f = ld_acq64(fl);
            const uint32_t rh = __ballot_sync(~0u, (uint32_t)f != 0), ro = __ballot_sync(~0u, (f >> 32) != 0);
            ready = __ffs(~rh) - 1;
            if (ready == 28) ready += (__ffs(~ro) - 1) >> 1;
            if (n < ready) break;
            if (i > 0x100000) __trap();
            __nanosleep(NS_F);
          }
          fence_async_gl();
        }
        const int s = n & 7;
        mbar_wait_sleep<NS_W>(sb + B_FEMPTY + 8 * s, ((n >> 3) & 1) ^ 1);
        u_bulk(sb + B_FFULL + 8 * s, 8192, sb + s * FST, src + n * 8192);
      }
      if (cg < 4) for (int i = 0; i < 4; i++) g_kv0[tb * 512 + cg * 128 + i * 32 + lane] = make_uint4(0, 0, 0, 0);
      uint32_t last = 0;
      if (lane == 0) { __threadfence(); last = atomicAdd(&g_done, 1) == gridDim.x - 1; __threadfence(); }
      if (__shfl_sync(~0u, last, 0)) {
        for (int i = lane; i < (64 + 32 * 64) / 4; i += 32) reinterpret_cast<uint4*>(g_flags)[i] = make_uint4(0, 0, 0, 0);
        if (lane == 0) g_done = 0;
      }
    }
  } else if (wg == 2) {
    asm volatile("setmaxnreg.inc.sync.aligned.u32 %0;" ::"n"(REG_GEMM));
    constexpr uint32_t H128 = dhi(1024, 1);
    float e[11] = {};
    if (cg < 4) {
#pragma unroll
      for (int i = 0; i < 4; i++) {
        const uint32_t a = sb + KV_OFF + i * 4096 + (tid & 127) * 32 + (tid & 4) * 4;
        sts128(a, wa[i].x, wa[i].z, wb[i].x, wb[i].z); sts128(a ^ 16, wa[i].y, wa[i].w, wb[i].y, wb[i].w); sts32(a + 16384, wz[i]);
      }
      asm volatile("fence.proxy.async.shared::cta;" ::: "memory");
      float d[12];
      zero(d);
      bar_sync(3);
      const uint32_t xl = dlo(sb + X_OFF + half * 65536, 16), wl = dlo(sb + KV_OFF, 16384);
#pragma unroll 1
      for (int j = 0; j < 4; j++) {
        mbar_wait(sb + B_XFULL + 32 * half + 8 * j, 0);
        wg_fence();
#pragma unroll
        for (int k = 0; k < 8; k++) mma_ss_t24(d, mk64(xl + j * 1024 + (k >> 2) * 512 + 2 * (k & 3), H128), KD(wl + j * 256 + 32 * k), 1);
        wg_commit();
      }
      wg_wait<0>(); pin(d);
      if ((tid & 127) == 0) EV(46);
      const float sc = cg < 2 ? 0.0625f : 1.f;
      const uint32_t w0 = packh(d[0] * sc, d[1] * sc), w1 = packh(d[4] * sc, d[5] * sc), w2 = packh(d[2] * sc, d[3] * sc), w3 = packh(d[6] * sc, d[7] * sc);
      st_rlx128(g_kv0 + tb * 512 + cg * 128 + (tid & 127), ~w0, ~w1, ~w2, ~w3);
      uint8_t* dst = g_kv + (tb * 2 + half) * 4096 + (cg >> 1) * 2048 + wq4 * 512 + ((lane * 8) ^ (lane & 16));
      stg64(dst, w0, w1); stg64(dst + 256, w2, w3);
      asm volatile("bar.arrive 4, 192;" ::: "memory");
      if ((tid & 127) == 0) EV(47);
#pragma unroll
      for (int i = 0; i < 11; i++) asm volatile("mov.b32 %0, %1;" : "=f"(e[i]) : "f"(d[i]));
    }
    {
      uint32_t r[4][4], pend = 15;
#pragma unroll 1
      for (int i = 0; pend && i < 0x100000; i++) {
#pragma unroll
        for (int j = 0; j < 4; j++) if (pend >> j & 1) ld_rlx128(r[j], g_kv0 + tb * 512 + j * 128 + (tid & 127), 1);
#pragma unroll
        for (int j = 0; j < 4; j++) if (__all_sync(~0u, min(min(r[j][0], r[j][1]), min(r[j][2], r[j][3])) != 0)) pend &= ~(1u << j);
      }
      if (cg < 4) bar_sync(3);
      const uint32_t a = sb + KV_OFF + wq4 * 512 + ((lane * 8) ^ (lane & 16));
#pragma unroll
      for (int j = 0; j < 4; j++) { sts64(a + (j & 1) * 4096 + (j >> 1) * 2048, ~r[j][0], ~r[j][1]); sts64(a + (j & 1) * 4096 + (j >> 1) * 2048 + 256, ~r[j][2], ~r[j][3]); }
      asm volatile("fence.proxy.async.shared::cta;" ::: "memory");
      bar_sync(3);
      if (tid == 256) { mbar_arrive(sb + B_KVFULL); EV(45); }
    }
    if (cg < 4) {
      g_kvb[(tb * 8 + half * 4 + wq4) * 64 + (cg >> 1) * 32 + lane] = make_uint4(pack2(e[0], e[1]), pack2(e[2], e[3]), pack2(e[4], e[5]), pack2(e[6], e[7]));
      uint32_t mx;
      if (cg < 2) {
        const float z0 = __shfl_sync(~0u, e[8], (lane & 7) * 4), z1 = __shfl_sync(~0u, e[10], (lane & 7) * 4);
        const float g = 1.f / (1.f + __expf((lane & 8) ? -z1 : -z0));
        if (lane < 16) g_gate[tb * 128 + half * 64 + wq4 * 16 + lane] = make_float2(g, 0.5f * (1.f - g));
        float n0 = sq4(e[0], e[1], e[4], e[5]), n1 = sq4(e[2], e[3], e[6], e[7]);
        n0 += __shfl_xor_sync(~0u, n0, 1); n1 += __shfl_xor_sync(~0u, n1, 1);
        n0 += __shfl_xor_sync(~0u, n0, 2); n1 += __shfl_xor_sync(~0u, n1, 2);
        mx = __reduce_max_sync(~0u, max(__float_as_uint(n0), __float_as_uint(n1)));
      } else {
        bool ok = true;
#pragma unroll
        for (int i = 0; i < 4; i++) {
          const int j = (i & 1) + (i >> 1) * 4;
          uint32_t c = max(__float_as_uint(e[j]) & 0x7fffffffu, __float_as_uint(e[j + 2]) & 0x7fffffffu);
          c = max(c, __shfl_xor_sync(~0u, c, 4)); c = max(c, __shfl_xor_sync(~0u, c, 8)); c = max(c, __shfl_xor_sync(~0u, c, 16));
          ok = ok && (c == 0 || (c >= 0x37800000u && c <= 0x47000000u));
        }
        mx = __all_sync(~0u, ok) ? 0 : 0x7f800001u;
      }
      if (lane == 0) sts32(sb + MISC_OFF + 48 + wq4 * 4, mx);
      asm volatile("bar.arrive 5, 160;" ::: "memory");
      if ((tid & 127) == 0) EV(52);
    }
    float d0[64], d1[64];
    zero(d0); zero(d1);
    if (QFIRST) mbar_wait(sb + B_WEMPTY + 24, 0);
    const uint32_t xl = dlo(sb + X_OFF, 16), wl = dlo(sb + W_OFF, 8192);
    uint8_t* const hdst = a_tb + wq4 * 256 + lane * 4;
    const uint32_t grow = sb + G_OFF + (wq4 * 16 + (lane >> 2)) * 8 + 4;
#pragma unroll 1
    for (int st = 0; st < 3; st++) {
#pragma unroll 1
      for (int kc = 0; kc < 8; kc++) {
        const int s = kc & 3;
        if (!QFIRST && st == 0) { mbar_wait(sb + B_XFULL + 8 * (kc >> 1), 0); mbar_wait(sb + B_XFULL + 32 + 8 * (kc >> 1), 0); }
        mbar_wait(sb + B_WFULL + 8 * s, (kc >> 2) & 1);
        const uint32_t a = xl + kc * 512, b = wl + s * 1024;
#pragma unroll
        for (int k = 0; k < 4; k++) {
          wg_fence();
          mma_ss_t128(d0, mk64(a + 2 * k, H128), mk64(b + 128 * k, H128), (kc | k) != 0);
          mma_ss_t128(d1, mk64(a + 4096 + 2 * k, H128), mk64(b + 128 * k, H128), (kc | k) != 0);
          wg_commit(); wg_wait<GW1>();
          if (GW1 && k == 0 && kc != 0 && lane == 0) mbar_arrive2(sb + B_WEMPTY + 8 * ((s + 3) & 3));
        }
        if (!GW1 && lane == 0) mbar_arrive2(sb + B_WEMPTY + 8 * s);
      }
      if (GW1) { wg_wait<0>(); if (lane == 0) mbar_arrive2(sb + B_WEMPTY + 8 * 3); }
      pin(d0); pin(d1);
      if (st == 0) { if (tid == 256) EV(8); mbar_wait(sb + B_GREADY, 0); }
      const int hc = st * 8 + cg;
      store_h(d0, __uint_as_float(lds32(grow)), __uint_as_float(lds32(grow + 64)), hdst + hc * 8192);
      store_h(d1, __uint_as_float(lds32(grow + 512)), __uint_as_float(lds32(grow + 576)), hdst + A_BYTES + hc * 8192);
      __syncwarp();
      if (lane == 0) mbar_arrive(sb + B_PUB + 8 * st);
      pin(d0); pin(d1);
    }
    {
#pragma unroll 1
      for (int kc = 0; kc < 8; kc++) {
        const int s = kc & 3;
        mbar_wait(sb + B_WFULL + 8 * s, (kc >> 2) & 1);
        const uint32_t a = xl + kc * 512 + half * 4096, b = wl + s * 1024;
#pragma unroll
        for (int k = 0; k < 4; k += 2) {
          wg_fence();
          mma_ss_t128(d0, mk64(a + 2 * k, H128), mk64(b + 128 * k, H128), (kc | k) != 0);
          mma_ss_t128(d0, mk64(a + 2 * k + 2, H128), mk64(b + 128 * k + 128, H128), 1);
          wg_commit(); wg_wait<GW1>();
          if (GW1 && k == 0 && kc != 0 && lane == 0) mbar_arrive2(sb + B_WEMPTY + 8 * ((s + 3) & 3));
        }
        if (!GW1 && lane == 0) mbar_arrive2(sb + B_WEMPTY + 8 * s);
      }
      wg_wait<0>();
      pin(d0);
      if (lane == 0) mbar_arrive(sb + B_FFN1);
      if (tid == 256) EV(12);
      const int hc = 24 + (cg >> 1);
      store_h(d0, __uint_as_float(lds32(grow + half * 512)), __uint_as_float(lds32(grow + half * 512 + 64)), hdst + half * A_BYTES + hc * 8192);
      __syncwarp();
      if (lane == 0) mbar_arrive(sb + B_PUB + 24);
      pin(d0);
    }
    const uint32_t al = dlo(sb, 1024), bl = dlo(sb + 8192, 8192);
    constexpr uint32_t HA = dhi(128, 0);
#pragma unroll 1
    for (int n = 0; n < 32; n++) {
      const int s = n & 7;
      mbar_wait_sleep<NS_G>(sb + B_FFULL + 8 * s, (n >> 3) & 1);
      const uint32_t a = al + s * (FST >> 4), b = bl + s * (FST >> 4);
#pragma unroll
      for (int k = 0; k < 4; k += FK) {
        wg_fence();
#pragma unroll
        for (int i = k; i < k + FK; i++) mma_ss_t128(d0, mk64(a + 128 * i, HA), mk64(b + 128 * i, H128), (n | i) != 0);
        wg_commit(); wg_wait<GW2>();
        if (GW2 && k == (GW2 - 1) * FK && n != 0 && lane == 0) mbar_arrive(sb + B_FEMPTY + 8 * ((s + 7) & 7));
      }
      if (!GW2 && lane == 0) mbar_arrive(sb + B_FEMPTY + 8 * s);
    }
    if (tid == 256) EV(18);
    {
#pragma unroll
      for (int s = 0; s < 4; s++) mbar_wait(sb + B_FFULL + 8 * s, 0);
      if (POLLG) mbar_wait_sleep<NS_G>(sb + B_KVEMPTY + 16, 1);
      if (tid == 256) EV(31);
      const uint8_t* src = a_tb + half * A_BYTES + 256 * 1024 + (tid & 127) * 16;
      const uint32_t dst = sb + (lane >> 4) * 1024 + wq4 * 256 + (lane & 15) * 16;
      uint32_t pend = 255, todo = 255, avail = 0, slot = sb + MISC_OFF;
#pragma unroll 1
      for (int n = 0; n < 8; n++) {
#pragma unroll 1
        for (int i = 0; !avail; i++) {
          uint32_t r[16][4];
#pragma unroll
          for (int j = 0; j < 16; j++) ld_rlx128(r[j], src + j * 2048, pend & (1u << (j >> 1)));
#pragma unroll
          for (int j = 0; j < 8; j++) if (pend >> j & 1) {
            const uint32_t (&u)[4] = r[2 * j], (&v)[4] = r[2 * j + 1];
            if (__all_sync(~0u, min(min(min(u[0], u[1]), min(u[2], u[3])), min(min(v[0], v[1]), min(v[2], v[3]))) != 0)) {
              stsm4(dst + (j >> 1) * FST + (j & 1) * 4096, ~u[0], ~u[1], ~u[2], ~u[3]);
              stsm4(dst + (j >> 1) * FST + (j & 1) * 4096 + 2048, ~v[0], ~v[1], ~v[2], ~v[3]);
              pend ^= 1u << j;
            }
          }
          if (i > 0x100000) pend = 0;
          asm volatile("fence.proxy.async.shared::cta;" ::: "memory");
          slot ^= 16;
          if (lane == 0) sts32(slot + wq4 * 4, pend);
          bar_sync(3);
          avail = todo & ~__reduce_or_sync(~0u, lds32(slot + (lane & 3) * 4));
          todo ^= avail;
        }
        const uint32_t j = __ffs(avail) - 1, o = (j >> 1) * (FST >> 4) + (j & 1) * 256;
        avail &= avail - 1;
        wg_fence();
        mma_ss_t128(d0, mk64(al + o, HA), mk64(bl + o, H128), 1);
        mma_ss_t128(d0, mk64(al + o + 128, HA), mk64(bl + o + 128, H128), 1);
        wg_commit();
      }
    }
    wg_wait<0>();
    pin(d0);
    if (tid == 256) EV(19);
    const uint32_t stg = sb + 4 * FST;
    const int r = wq4 * 16 + (lane & 7) + ((lane >> 3) & 1) * 8;
#pragma unroll
    for (int j = 0; j < 8; j++) {
      const int c16 = (2 * j + (lane >> 4)) & 7;
      const uint32_t ad = stg + (j >> 2) * 8192 + r * 128 + ((c16 ^ (r & 7)) << 4);
      stsm4(ad, pack2(d0[8 * j], d0[8 * j + 1]), pack2(d0[8 * j + 2], d0[8 * j + 3]), pack2(d0[8 * j + 4], d0[8 * j + 5]), pack2(d0[8 * j + 6], d0[8 * j + 7]));
    }
    asm volatile("fence.proxy.async.shared::cta;" ::: "memory");
    bar_sync(3);
    if (tid == 256) {
      asm volatile("cp.async.bulk.tensor.3d.global.shared::cta.bulk_group [%0, {%2, %3, %4}], [%1];" ::"l"(&mp.out), "r"(stg), "r"(0), "r"(tb * 128 + half * 64), "r"(cg & 6) : "memory");
      asm volatile("cp.async.bulk.commit_group;" ::: "memory");
      asm volatile("cp.async.bulk.wait_group.read 0;" ::: "memory");
      EV(20);
    }
  } else {
    asm volatile("setmaxnreg.inc.sync.aligned.u32 %0;" ::"n"(REG_ATT));
    constexpr uint32_t H128 = dhi(1024, 1);
    const uint32_t xl = dlo(sb + X_OFF + wg * 65536, 16);
    uint32_t qh[4][4], qb[4][4];
    float qn;
    {
      float d[32];
      zero(d);
      const uint32_t wl = dlo(sb + W_OFF, 8192);
#pragma unroll 1
      for (int s = 0; s < 4; s++) {
        if (WQCP) {
          asm volatile("cp.async.wait_group 3;\ncp.async.commit_group;\nfence.proxy.async.shared::cta;\nbar.sync 6, 256;" ::: "memory");
        } else mbar_wait(sb + B_WQ + 8 * s, 0);
        mbar_wait(sb + B_XFULL + 32 * wg + 8 * s, 0);
        wg_fence();
#pragma unroll
        for (int k = 0; k < 8; k++) mma_ss_t64(d, mk64(xl + (2 * s + (k >> 2)) * 512 + 2 * (k & 3), H128), mk64(wl + s * 1024 + 128 * k, H128), 1);
        wg_commit();
        wg_wait<0>();
        if (lane == 0) mbar_arrive(sb + B_WEMPTY + 8 * s);
      }
      pin(d);
      if (tid == 0) EV(44);
      uint32_t nm = 0;
#pragma unroll
      for (int h = 0; h < 4; h++) {
        const float* dh = d + 8 * h;
#pragma unroll
        for (int i = 0; i < 4; i++) {
          const float c = (i & 1) ? QS / 32.f : QS * 16.f;
          qh[h][i] = packh(dh[2 * i] * c, dh[2 * i + 1] * c);
          qb[h][i] = pack2(dh[2 * i], dh[2 * i + 1]);
        }
        float n0 = sq4(dh[0], dh[1], dh[4], dh[5]), n1 = sq4(dh[2], dh[3], dh[6], dh[7]);
        n0 += __shfl_xor_sync(~0u, n0, 1); n1 += __shfl_xor_sync(~0u, n1, 1);
        n0 += __shfl_xor_sync(~0u, n0, 2); n1 += __shfl_xor_sync(~0u, n1, 2);
        nm = max(nm, max(__float_as_uint(n0), __float_as_uint(n1)));
      }
      qn = __uint_as_float(nm) * (QS * QS);
    }
    if (tid == 0) EV(3);
    mbar_wait(sb + B_KVFULL, 0);
    if (tid == 0) { EV(5); EVC(0); }
    uint8_t* odst = a_tb + wg * A_BYTES + (224 + cg * 4) * 1024 + wq4 * 256 + lane * 4;
    attn_passes(qh, qb, qn, odst, wg);
  }
}

typedef CUresult (*EncodeFn)(CUtensorMap*, CUtensorMapDataType, cuuint32_t, void*, const cuuint64_t*, const cuuint64_t*, const cuuint32_t*, const cuuint32_t*,
                             CUtensorMapInterleave, CUtensorMapSwizzle, CUtensorMapL2promotion, CUtensorMapFloatOOBfill);

void make_map(EncodeFn fn, CUtensorMap* m, const void* p, uint64_t cols, uint64_t rows, uint32_t bc, uint32_t br, CUtensorMapSwizzle sw) {
  cuuint64_t dims[2] = {cols, rows}, strides[1] = {cols * 2};
  cuuint32_t box[2] = {bc, br}, es[2] = {1, 1};
  fn(m, CU_TENSOR_MAP_DATA_TYPE_BFLOAT16, 2, const_cast<void*>(p), dims, strides, box, es, CU_TENSOR_MAP_INTERLEAVE_NONE, sw,
     CU_TENSOR_MAP_L2_PROMOTION_L2_128B, CU_TENSOR_MAP_FLOAT_OOB_FILL_NONE);
}

void make_map3(EncodeFn fn, CUtensorMap* m, const void* p, uint64_t bw, uint64_t nblk, uint64_t rows, uint32_t bc, uint32_t br, CUtensorMapSwizzle sw) {
  cuuint64_t dims[3] = {bw, rows, nblk}, strides[2] = {bw * nblk * 2, bw * 2};
  cuuint32_t box[3] = {bc, br, 2}, es[3] = {1, 1, 1};
  fn(m, CU_TENSOR_MAP_DATA_TYPE_BFLOAT16, 3, const_cast<void*>(p), dims, strides, box, es, CU_TENSOR_MAP_INTERLEAVE_NONE, sw,
     CU_TENSOR_MAP_L2_PROMOTION_L2_128B, CU_TENSOR_MAP_FLOAT_OOB_FILL_NONE);
}

void make_map4(EncodeFn fn, CUtensorMap* m, const void* p, uint64_t rows, uint64_t rg) {
  cuuint64_t dims[4] = {64, rg, rows / rg, 8}, strides[3] = {1024, rg * 1024, 128};
  cuuint32_t box[4] = {64, 32, 2, 2}, es[4] = {1, 1, 1, 1};
  fn(m, CU_TENSOR_MAP_DATA_TYPE_BFLOAT16, 4, const_cast<void*>(p), dims, strides, box, es, CU_TENSOR_MAP_INTERLEAVE_NONE, CU_TENSOR_MAP_SWIZZLE_128B,
     CU_TENSOR_MAP_L2_PROMOTION_L2_128B, CU_TENSOR_MAP_FLOAT_OOB_FILL_NONE);
}

}

extern "C" void kernel_launch(void* const* d_in, const int* in_sizes, int n_in, void* d_out, int out_size) {
  void* fp = nullptr;
  cudaDriverEntryPointQueryResult qr;
  cudaGetDriverEntryPoint("cuTensorMapEncodeTiled", &fp, cudaEnableDefault, &qr);
  EncodeFn fn = (EncodeFn)fp;
  Maps mp;
  make_map3(fn, &mp.x, d_in[0], 64, 8, S_, 64, 64, CU_TENSOR_MAP_SWIZZLE_128B);
  make_map(fn, &mp.wq, d_in[1], D_, D_, 64, 128, CU_TENSOR_MAP_SWIZZLE_128B);
  make_map4(fn, &mp.wo, d_in[4], D_, 64);
  make_map(fn, &mp.wg, d_in[6], F_, D_, 64, 64, CU_TENSOR_MAP_SWIZZLE_128B);
  make_map(fn, &mp.wu, d_in[7], F_, D_, 64, 64, CU_TENSOR_MAP_SWIZZLE_128B);
  make_map4(fn, &mp.wd, d_in[8], F_, 32);
  make_map3(fn, &mp.out, d_out, 64, 8, S_, 64, 64, CU_TENSOR_MAP_SWIZZLE_128B);
  cudaFuncSetAttribute(fused_kernel, cudaFuncAttributeMaxDynamicSharedMemorySize, SMEM_BYTES);
  fused_kernel<<<128, 512, SMEM_BYTES, cudaStreamPerThread>>>(mp, (const uint16_t*)d_in[9], (const uint4*)d_in[2], (const uint4*)d_in[3], (const uint8_t*)d_in[8], (const uint8_t*)d_in[4], (const uint8_t*)d_in[1]);
}
```

```cpp
#include <cuda_runtime.h>
#include <cuda_bf16.h>
#include <cuda.h>
#include <stdint.h>

#define DEG 2
#define REG_ATT 160
#define REG_GEMM 160
#define REG_PROD 32
#define FORCE_SLOW 0
#define NS_W 100
#define NS_KV 200
#define NS_F 200
#define NS_G 50
#define GW1 0
#define GW2 1
#define HINT 4000
#define EXP 0
#define PRE 1
#define NDEF 0
#define EPI 1
#define FK 2
#define GSL 1
#define QFIRST 1

namespace {

constexpr int S_ = 2048, D_ = 512, F_ = 1792;
constexpr float QS = 0.25f * 1.4426950408889634f;

constexpr uint32_t sb = 1024;
constexpr uint32_t X_OFF = 0;
constexpr uint32_t W_OFF = 131072;
constexpr uint32_t KV_OFF = 196608;
constexpr uint32_t ONES_OFF = 229376;
constexpr uint32_t G_OFF = 229888;
constexpr uint32_t MISC_OFF = 231552;
constexpr uint32_t BAR_OFF = 231616;
constexpr uint32_t B_XFULL = BAR_OFF;
constexpr uint32_t B_PUB = B_XFULL + 64;
constexpr uint32_t B_GREADY = B_XFULL + 128;
constexpr uint32_t B_FFN1 = B_GREADY + 8;
constexpr uint32_t B_WFULL = B_FFN1 + 8;
constexpr uint32_t B_WEMPTY = B_WFULL + 32;
constexpr uint32_t B_KVFULL = B_WEMPTY + 32;
constexpr uint32_t B_KVEMPTY = B_KVFULL + 32;
constexpr uint32_t B_FFULL = B_KVEMPTY + 32;
constexpr uint32_t B_FEMPTY = B_FFULL + 64;
constexpr uint32_t B_WQ = B_FEMPTY + 64;
constexpr uint32_t B_TAIL = B_WQ + 32;
constexpr uint32_t B_Q = B_TAIL + 8;
constexpr uint32_t SMEM_BYTES = B_Q + 64;
constexpr uint32_t FST = 24576;
static_assert(SMEM_BYTES <= 232448, "smem");

constexpr int A_BYTES = 288 * 1024;
__device__ __align__(1024) uint8_t g_kv[32 * 4096];
__device__ uint4 g_kv0[16 * 512];
__device__ uint4 g_kvb[128 * 64];
__device__ __align__(1024) float2 g_gate[S_];
__device__ __align__(1024) uint8_t g_a[32 * A_BYTES];
__device__ __align__(256) uint32_t g_flags[64 + 32 * 64];
__device__ uint32_t g_done;

#define EV(i)
#define EVC(i)
struct Maps { CUtensorMap x, wq, wo, wg, wu, wd, out; };

__device__ __forceinline__ void wg_fence() { asm volatile("wgmma.fence.sync.aligned;" ::: "memory"); }
__device__ __forceinline__ void wg_commit() { asm volatile("wgmma.commit_group.sync.aligned;" ::: "memory"); }
template <int N> __device__ __forceinline__ void wg_wait() { asm volatile("wgmma.wait_group.sync.aligned %0;" ::"n"(N) : "memory"); }
template <int N> __device__ __forceinline__ void pin(float (&d)[N]) {
#pragma unroll
  for (int i = 0; i < N; i++) asm volatile("" : "+f"(d[i])::"memory");
}
template <int N> __device__ __forceinline__ void pinu(uint32_t (&d)[N]) {
#pragma unroll
  for (int i = 0; i < N; i++) asm volatile("" : "+r"(d[i])::"memory");
}
template <int N> __device__ __forceinline__ void zero(float (&d)[N]) {
#pragma unroll
  for (int i = 0; i < N; i++) d[i] = 0.f;
  pin(d);
}
__device__ __forceinline__ uint64_t mk64(uint32_t lo, uint32_t hi) { return ((uint64_t)hi << 32) | lo; }
__host__ __device__ constexpr uint32_t dhi(uint32_t sbo, uint32_t sw) { return (sbo >> 4) | (sw << 30); }
__device__ __forceinline__ uint32_t dlo(uint32_t addr, uint32_t lbo) { return (addr >> 4) | ((lbo >> 4) << 16); }

__device__ __forceinline__ void mbar_init(uint32_t b, uint32_t n) { asm volatile("mbarrier.init.shared::cta.b64 [%0], %1;" ::"r"(b), "r"(n) : "memory"); }
__device__ __forceinline__ void mbar_arrive(uint32_t b) { asm volatile("mbarrier.arrive.shared::cta.b64 _, [%0];" ::"r"(b) : "memory"); }
__device__ __forceinline__ void mbar_arrive2(uint32_t b) { asm volatile("mbarrier.arrive.shared::cta.b64 _, [%0], 2;" ::"r"(b) : "memory"); }
__device__ __forceinline__ void mbar_expect(uint32_t b, uint32_t bytes) { asm volatile("mbarrier.arrive.expect_tx.shared::cta.b64 _, [%0], %1;" ::"r"(b), "r"(bytes) : "memory"); }
__device__ __forceinline__ void mbar_wait(uint32_t b, uint32_t parity) {
  asm volatile(
      "{\n.reg .pred p;\n.reg .u32 c;\n"
      "mbarrier.try_wait.parity.shared::cta.b64 p, [%0], %1;\n"
      "@p bra DONE;\n"
      "mov.u32 c, 0;\n"
      "SPIN:\n"
      "mbarrier.try_wait.parity.shared::cta.b64 p, [%0], %1;\n"
      "@p bra DONE;\n"
      "add.u32 c, c, 1;\n"
      "setp.lt.u32 p, c, 0x100000;\n"
      "@p bra SPIN;\n"
      "trap;\n"
      "DONE:\n}\n" ::"r"(b), "r"(parity) : "memory");
}
template <int NS> __device__ __forceinline__ void mbar_wait_sleep(uint32_t b, uint32_t parity) {
  asm volatile(
      "{\n.reg .pred p;\n.reg .u32 c;\n"
      "mov.u32 c, 0;\n"
      "SPIN:\n"
      "mbarrier.try_wait.parity.shared::cta.b64 p, [%0], %1, %2;\n"
      "@p bra.uni DONE;\n"
      "add.u32 c, c, 1;\n"
      "setp.lt.u32 p, c, 0x40000;\n"
      "@p bra.uni SPIN;\n"
      "trap;\n"
      "DONE:\n}\n" ::"r"(b), "r"(parity), "n"(HINT) : "memory");
  return;
  asm volatile(
      "{\n.reg .pred p;\n.reg .u32 c;\n"
      "mov.u32 c, 0;\n"
      "SPIN:\n"
      "mbarrier.test_wait.parity.shared::cta.b64 p, [%0], %1;\n"
      "@p bra.uni DONE;\n"
      "nanosleep.u32 %2;\n"
      "add.u32 c, c, 1;\n"
      "setp.lt.u32 p, c, 0x100000;\n"
      "@p bra.uni SPIN;\n"
      "trap;\n"
      "DONE:\n}\n" ::"r"(b), "r"(parity), "n"(NS) : "memory");
}
#define ELECT "{\n.reg .pred p;\nelect.sync _|p, 0xffffffff;\n@p mbarrier.arrive.expect_tx.shared::cta.b64 _, [%0], %1;\n"
__device__ __forceinline__ void u_tma3d(uint32_t bar, uint32_t bytes, uint32_t dst, const CUtensorMap* m, int c0, int c1, int c2) {
  asm volatile(ELECT "@p cp.async.bulk.tensor.3d.shared::cluster.global.mbarrier::complete_tx::bytes [%2], [%3, {%4, %5, %6}], [%0];\n}\n" ::"r"(bar), "r"(bytes), "r"(dst), "l"(m), "r"(c0), "r"(c1), "r"(c2) : "memory");
}
__device__ __forceinline__ void u_tma4d(uint32_t bar, uint32_t bytes, uint32_t dst, const CUtensorMap* m, int c1, int c2, int c3) {
  asm volatile(ELECT "@p cp.async.bulk.tensor.4d.shared::cluster.global.mbarrier::complete_tx::bytes [%2], [%3, {0, %4, %5, %6}], [%0];\n}\n" ::"r"(bar), "r"(bytes), "r"(dst), "l"(m), "r"(c1), "r"(c2), "r"(c3) : "memory");
}
__device__ __forceinline__ void u_tma2d(uint32_t bar, uint32_t bytes, uint32_t dst, const CUtensorMap* m, int c0, int c1) {
  asm volatile(ELECT "@p cp.async.bulk.tensor.2d.shared::cluster.global.mbarrier::complete_tx::bytes [%2], [%3, {%4, %5}], [%0];\n}\n" ::"r"(bar), "r"(bytes), "r"(dst), "l"(m), "r"(c0), "r"(c1) : "memory");
}
__device__ __forceinline__ void u_tma2d_pair(uint32_t bar, uint32_t dst, const CUtensorMap* m0, const CUtensorMap* m1, int c0, int c1, int c1b) {
  asm volatile(ELECT "@p cp.async.bulk.tensor.2d.shared::cluster.global.mbarrier::complete_tx::bytes [%2], [%3, {%5, %6}], [%0];\n"
               "@p cp.async.bulk.tensor.2d.shared::cluster.global.mbarrier::complete_tx::bytes [%2 + 8192], [%4, {%5, %7}], [%0];\n}\n" ::"r"(bar), "r"(16384), "r"(dst), "l"(m0), "l"(m1), "r"(c0), "r"(c1), "r"(c1b) : "memory");
}
__device__ __forceinline__ void u_bulk(uint32_t bar, uint32_t bytes, uint32_t dst, const void* src) {
  asm volatile(ELECT "@p cp.async.bulk.shared::cluster.global.mbarrier::complete_tx::bytes [%2], [%3], %1, [%0];\n}\n" ::"r"(bar), "r"(bytes), "r"(dst), "l"(src) : "memory");
}
__device__ __forceinline__ void u_prefetch(const void* src, uint32_t bytes) {
  asm volatile("{\n.reg .pred p;\nelect.sync _|p, 0xffffffff;\n@p cp.async.bulk.prefetch.L2.global [%0], %1;\n}\n" ::"l"(src), "r"(bytes) : "memory");
}
__device__ __forceinline__ void fence_gpu() { asm volatile("fence.acq_rel.gpu;" ::: "memory"); }
__device__ __forceinline__ void st_rlx(uint32_t* p, uint32_t v) { asm volatile("st.relaxed.gpu.global.u32 [%0], %1;" ::"l"(p), "r"(v) : "memory"); }
__device__ __forceinline__ void st_rlx64(void* p, uint32_t a, uint32_t b) { asm volatile("st.relaxed.gpu.global.v2.u32 [%0], {%1, %2};" ::"l"(p), "r"(a), "r"(b) : "memory"); }
__device__ __forceinline__ void st_rlx128(void* p, uint32_t a, uint32_t b, uint32_t c, uint32_t d) { asm volatile("st.relaxed.gpu.global.v4.u32 [%0], {%1, %2, %3, %4};" ::"l"(p), "r"(a), "r"(b), "r"(c), "r"(d) : "memory"); }
__device__ __forceinline__ void ld_rlx128(uint32_t (&v)[4], const void* p, uint32_t c) {
  asm volatile("{\n.reg .pred p;\nsetp.ne.u32 p, %5, 0;\nmov.u32 %0, 0;\nmov.u32 %1, 0;\nmov.u32 %2, 0;\nmov.u32 %3, 0;\n@p ld.relaxed.gpu.global.v4.u32 {%0, %1, %2, %3}, [%4];\n}" : "=r"(v[0]), "=r"(v[1]), "=r"(v[2]), "=r"(v[3]) : "l"(p), "r"(c) : "memory");
}
__device__ __forceinline__ uint64_t ld_acq64(const uint32_t* p) { uint64_t v; asm volatile("ld.acquire.gpu.global.u64 %0, [%1];" : "=l"(v) : "l"(p) : "memory"); return v; }
__device__ __forceinline__ void tma2d(uint32_t dst, const CUtensorMap* m, int c0, int c1, uint32_t bar) {
  asm volatile("cp.async.bulk.tensor.2d.shared::cluster.global.mbarrier::complete_tx::bytes [%0], [%1, {%3, %4}], [%2];" ::"r"(dst), "l"(m), "r"(bar), "r"(c0), "r"(c1) : "memory");
}
__device__ __forceinline__ void bulk_ld(uint32_t dst, const void* src, uint32_t bytes, uint32_t bar) {
  asm volatile("cp.async.bulk.shared::cluster.global.mbarrier::complete_tx::bytes [%0], [%1], %2, [%3];" ::"r"(dst), "l"(src), "r"(bytes), "r"(bar) : "memory");
}
__device__ __forceinline__ void l2_prefetch(const void* src, uint32_t bytes) {
  asm volatile("cp.async.bulk.prefetch.L2.global [%0], %1;" ::"l"(src), "r"(bytes) : "memory");
}
__device__ __forceinline__ uint32_t ld_acq(const uint32_t* p) { uint32_t v; asm volatile("ld.acquire.gpu.global.u32 %0, [%1];" : "=r"(v) : "l"(p) : "memory"); return v; }
__device__ __forceinline__ void st_rel(uint32_t* p, uint32_t v) { asm volatile("st.release.gpu.global.u32 [%0], %1;" ::"l"(p), "r"(v) : "memory"); }
__device__ __forceinline__ void fence_async_all() { asm volatile("fence.proxy.async;" ::: "memory"); }
__device__ __forceinline__ void fence_async_gl() { asm volatile("fence.proxy.async.global;" ::: "memory"); }
__device__ __forceinline__ void bar_sync(int id) { asm volatile("bar.sync %0, 128;" ::"r"(id) : "memory"); }
__device__ __forceinline__ uint32_t pack2(float lo, float hi) { uint32_t r; asm("cvt.rn.bf16x2.f32 %0, %1, %2;" : "=r"(r) : "f"(hi), "f"(lo)); return r; }
__device__ __forceinline__ float ex2(float a) { float r; asm("ex2.approx.ftz.f32 %0, %1;" : "=f"(r) : "f"(a)); return r; }
__device__ __forceinline__ float sq4(float a, float b, float c, float d) { return fmaf(a, a, b * b) + fmaf(c, c, d * d); }
__device__ __forceinline__ void stg32(void* p, uint32_t v) { asm volatile("st.global.u32 [%0], %1;" ::"l"(p), "r"(v) : "memory"); }
__device__ __forceinline__ void stg64(void* p, uint32_t a, uint32_t b) { asm volatile("st.global.v2.u32 [%0], {%1, %2};" ::"l"(p), "r"(a), "r"(b) : "memory"); }
__device__ __forceinline__ void sts128(uint32_t a, uint32_t x, uint32_t y, uint32_t z, uint32_t w) { asm volatile("st.shared.v4.u32 [%0], {%1, %2, %3, %4};" ::"r"(a), "r"(x), "r"(y), "r"(z), "r"(w) : "memory"); }
__device__ __forceinline__ void stsm4(uint32_t a, uint32_t x, uint32_t y, uint32_t z, uint32_t w) { asm volatile("stmatrix.sync.aligned.m8n8.x4.shared.b16 [%0], {%1,%2,%3,%4};" ::"r"(a), "r"(x), "r"(y), "r"(z), "r"(w) : "memory"); }
__device__ __forceinline__ void sts64(uint32_t a, uint32_t x, uint32_t y) { asm volatile("st.shared.v2.u32 [%0], {%1, %2};" ::"r"(a), "r"(x), "r"(y) : "memory"); }
__device__ __forceinline__ void sts32(uint32_t a, uint32_t v) { asm volatile("st.shared.u32 [%0], %1;" ::"r"(a), "r"(v) : "memory"); }
__device__ __forceinline__ uint32_t lds32(uint32_t a) { uint32_t v; asm volatile("ld.shared.u32 %0, [%1];" : "=r"(v) : "r"(a) : "memory"); return v; }

__device__ __forceinline__ void mma_qk(uint32_t (&d)[16], const uint32_t (&a)[4], uint64_t b) {
  asm volatile("{\n.reg .pred p;\nsetp.ne.b32 p, 0, 0;\n"
    "wgmma.mma_async.sync.aligned.m64n64k16.f16.f16.f16 {%0,%1,%2,%3,%4,%5,%6,%7,%8,%9,%10,%11,%12,%13,%14,%15}, {%16,%17,%18,%19}, %20, p, 1, 1, 0;\n}\n"
    : "+r"(d[0]),"+r"(d[1]),"+r"(d[2]),"+r"(d[3]),"+r"(d[4]),"+r"(d[5]),"+r"(d[6]),"+r"(d[7]),"+r"(d[8]),"+r"(d[9]),"+r"(d[10]),"+r"(d[11]),"+r"(d[12]),"+r"(d[13]),"+r"(d[14]),"+r"(d[15]) : "r"(a[0]),"r"(a[1]),"r"(a[2]),"r"(a[3]),"l"(b));
}
__device__ __forceinline__ void mma_pv(uint32_t (&d)[6], const uint32_t (&a)[4], uint64_t b) {
  asm volatile("{\n.reg .pred p;\nsetp.ne.b32 p, 1, 0;\n"
    "wgmma.mma_async.sync.aligned.m64n24k16.f16.f16.f16 {%0,%1,%2,%3,%4,%5}, {%6,%7,%8,%9}, %10, p, 1, 1, 1;\n}\n"
    : "+r"(d[0]),"+r"(d[1]),"+r"(d[2]),"+r"(d[3]),"+r"(d[4]),"+r"(d[5]) : "r"(a[0]),"r"(a[1]),"r"(a[2]),"r"(a[3]),"l"(b));
}
__device__ __forceinline__ void mma_pv0(uint32_t (&d)[6], const uint32_t (&a)[4], uint64_t b) {
  asm volatile("{\n.reg .pred p;\nsetp.ne.b32 p, 0, 0;\n"
    "wgmma.mma_async.sync.aligned.m64n24k16.f16.f16.f16 {%0,%1,%2,%3,%4,%5}, {%6,%7,%8,%9}, %10, p, 1, 1, 1;\n}\n"
    : "+r"(d[0]),"+r"(d[1]),"+r"(d[2]),"+r"(d[3]),"+r"(d[4]),"+r"(d[5]) : "r"(a[0]),"r"(a[1]),"r"(a[2]),"r"(a[3]),"l"(b));
}
__device__ __forceinline__ void mma_ss_t128(float (&d)[64], uint64_t a, uint64_t b, int acc) {
  asm volatile("{\n.reg .pred p;\nsetp.ne.b32 p, %66, 0;\n"
    "wgmma.mma_async.sync.aligned.m64n128k16.f32.bf16.bf16 {%0,%1,%2,%3,%4,%5,%6,%7,%8,%9,%10,%11,%12,%13,%14,%15,%16,%17,%18,%19,%20,%21,%22,%23,%24,%25,%26,%27,%28,%29,%30,%31,%32,%33,%34,%35,%36,%37,%38,%39,%40,%41,%42,%43,%44,%45,%46,%47,%48,%49,%50,%51,%52,%53,%54,%55,%56,%57,%58,%59,%60,%61,%62,%63}, %64, %65, p, 1, 1, 0, 1;\n}\n"
    : "+f"(d[0]),"+f"(d[1]),"+f"(d[2]),"+f"(d[3]),"+f"(d[4]),"+f"(d[5]),"+f"(d[6]),"+f"(d[7]),"+f"(d[8]),"+f"(d[9]),"+f"(d[10]),"+f"(d[11]),"+f"(d[12]),"+f"(d[13]),"+f"(d[14]),"+f"(d[15]),"+f"(d[16]),"+f"(d[17]),"+f"(d[18]),"+f"(d[19]),"+f"(d[20]),"+f"(d[21]),"+f"(d[22]),"+f"(d[23]),"+f"(d[24]),"+f"(d[25]),"+f"(d[26]),"+f"(d[27]),"+f"(d[28]),"+f"(d[29]),"+f"(d[30]),"+f"(d[31]),"+f"(d[32]),"+f"(d[33]),"+f"(d[34]),"+f"(d[35]),"+f"(d[36]),"+f"(d[37]),"+f"(d[38]),"+f"(d[39]),"+f"(d[40]),"+f"(d[41]),"+f"(d[42]),"+f"(d[43]),"+f"(d[44]),"+f"(d[45]),"+f"(d[46]),"+f"(d[47]),"+f"(d[48]),"+f"(d[49]),"+f"(d[50]),"+f"(d[51]),"+f"(d[52]),"+f"(d[53]),"+f"(d[54]),"+f"(d[55]),"+f"(d[56]),"+f"(d[57]),"+f"(d[58]),"+f"(d[59]),"+f"(d[60]),"+f"(d[61]),"+f"(d[62]),"+f"(d[63]) : "l"(a),"l"(b),"r"(acc));
}
__device__ __forceinline__ void mma_ss_t64(float (&d)[32], uint64_t a, uint64_t b, int acc) {
  asm volatile("{\n.reg .pred p;\nsetp.ne.b32 p, %34, 0;\n"
    "wgmma.mma_async.sync.aligned.m64n64k16.f32.bf16.bf16 {%0,%1,%2,%3,%4,%5,%6,%7,%8,%9,%10,%11,%12,%13,%14,%15,%16,%17,%18,%19,%20,%21,%22,%23,%24,%25,%26,%27,%28,%29,%30,%31}, %32, %33, p, 1, 1, 0, 1;\n}\n"
    : "+f"(d[0]),"+f"(d[1]),"+f"(d[2]),"+f"(d[3]),"+f"(d[4]),"+f"(d[5]),"+f"(d[6]),"+f"(d[7]),"+f"(d[8]),"+f"(d[9]),"+f"(d[10]),"+f"(d[11]),"+f"(d[12]),"+f"(d[13]),"+f"(d[14]),"+f"(d[15]),"+f"(d[16]),"+f"(d[17]),"+f"(d[18]),"+f"(d[19]),"+f"(d[20]),"+f"(d[21]),"+f"(d[22]),"+f"(d[23]),"+f"(d[24]),"+f"(d[25]),"+f"(d[26]),"+f"(d[27]),"+f"(d[28]),"+f"(d[29]),"+f"(d[30]),"+f"(d[31]) : "l"(a),"l"(b),"r"(acc));
}
__device__ __forceinline__ void mma_ss_t24(float (&d)[12], uint64_t a, uint64_t b, int acc) {
  asm volatile("{\n.reg .pred p;\nsetp.ne.b32 p, %14, 0;\n"
    "wgmma.mma_async.sync.aligned.m64n24k16.f32.bf16.bf16 {%0,%1,%2,%3,%4,%5,%6,%7,%8,%9,%10,%11}, %12, %13, p, 1, 1, 0, 1;\n}\n"
    : "+f"(d[0]),"+f"(d[1]),"+f"(d[2]),"+f"(d[3]),"+f"(d[4]),"+f"(d[5]),"+f"(d[6]),"+f"(d[7]),"+f"(d[8]),"+f"(d[9]),"+f"(d[10]),"+f"(d[11]) : "l"(a),"l"(b),"r"(acc));
}

__device__ __forceinline__ uint32_t hfma2(uint32_t a, uint32_t b, uint32_t c) { uint32_t r; asm("fma.rn.f16x2 %0, %1, %2, %3;" : "=r"(r) : "r"(a), "r"(b), "r"(c)); return r; }
__device__ __forceinline__ uint32_t packh(float lo, float hi) { uint32_t r; asm("cvt.rn.f16x2.f32 %0, %1, %2;" : "=r"(r) : "f"(hi), "f"(lo)); return r; }
__device__ __forceinline__ void unpackh(uint32_t a, float& lo, float& hi) { asm("{\n.reg .b16 l, h;\nmov.b32 {l, h}, %2;\ncvt.f32.f16 %0, l;\ncvt.f32.f16 %1, h;\n}" : "=f"(lo), "=f"(hi) : "r"(a)); }
__device__ __forceinline__ uint32_t exp2_mufu(uint32_t s) { uint32_t r; asm("ex2.approx.f16x2 %0, %1;" : "=r"(r) : "r"(s)); return r; }
__device__ __forceinline__ uint32_t exp2_fma(uint32_t s) {
  uint32_t t, u;
  asm("fma.rn.relu.f16x2 %0, %1, %2, %3;" : "=r"(t) : "r"(s), "r"(0x02000200u), "r"(0x000a000au));
  asm("mul.rn.f16x2 %0, %1, %2;" : "=r"(u) : "r"(s), "r"(0x02000200u));
  const uint32_t f = hfma2(u, 0xF800F800u, s);
  const uint32_t y = hfma2(hfma2(f, 0x45614561u, 0x27f627f6u), f, 0x05aa05aau);
  return y + (t << 10);
}
template <int J> __device__ __forceinline__ void sm_unit(const uint32_t (&s)[16], uint32_t (&p)[4]) {
  p[0] = exp2_mufu(s[4 * J]); p[1] = exp2_fma(s[4 * J + 1]); p[2] = exp2_mufu(s[4 * J + 2]); p[3] = exp2_fma(s[4 * J + 3]);
}

#define KD(lo) mk64((lo), dhi(256, 3))
#define VO(x) ((uint32_t)(x) - ((uint32_t)(x) << 16))

__device__ __forceinline__ void flush(uint32_t (&a)[6], uint32_t (&o)[6]) {
#pragma unroll
  for (int i = 0; i < 6; i++) asm volatile("add.rn.f16x2 %0, %0, %1;" : "+r"(a[i]) : "r"(o[i]) : "memory");
}
__device__ __forceinline__ void attn_fast(const uint32_t (&q0)[4], const uint32_t (&q1)[4], uint32_t (&a0)[6], uint32_t (&a1)[6], int lane) {
  const uint32_t kvfull = sb + B_KVFULL, kvempty = sb + B_KVEMPTY;
  const uint32_t kbase = dlo(sb + KV_OFF, 16), vbase = dlo(sb + KV_OFF, ONES_OFF - KV_OFF);
  uint32_t s0[16] = {}, s1[16] = {}, o0[6] = {}, o1[6] = {};
  pinu(s0); pinu(s1); pinu(o0); pinu(o1);
  {
    uint32_t p0[4]={0,0,0,0}; pinu(p0);
    uint32_t p1[4]={0,0,0,0}; pinu(p1);
    uint32_t p2[4]={0,0,0,0}; pinu(p2);
    uint32_t p3[4]={0,0,0,0}; pinu(p3);
    wg_fence(); mma_qk(s0, q0, KD(kbase)); wg_commit(); wg_wait<0>(); pinu(s0);
    uint32_t vprev = vbase - VO(512);
#pragma unroll 1
    for (int it = 0; it < 8; it++) {
      const uint32_t sA = (it & 1) * 2, ph = (it >> 1) & 1, phn = ((it + 1) >> 1) & 1;
      const uint32_t kcur = kbase + sA * 512, knxt = kbase + (sA ^ 2) * 512, vcur = vbase + VO(sA * 512);
      wg_fence();
      mma_qk(s1,q1,KD(kcur+0));
      mma_pv0(o1,p2,KD(vprev+VO(960)));
      mma_pv(o1,p3,KD(vprev+VO(992)));
      wg_commit();
      flush(a0, o0);
      sm_unit<0>(s0,p0);
      sm_unit<1>(s0,p1);
      wg_fence();
      mma_pv0(o0,p0,KD(vcur+VO(128)));
      mma_pv(o0,p1,KD(vcur+VO(160)));
      wg_commit();
      wg_wait<1>();
      if (!(EXP & 32) && lane==0 && it!=0) mbar_arrive(kvempty+8*((sA^2)+1));
      sm_unit<2>(s0,p2);
      sm_unit<3>(s0,p3);
      wg_fence();
      mma_qk(s0,q0,KD(kcur+256));
      mma_pv(o0,p2,KD(vcur+VO(192)));
      mma_pv(o0,p3,KD(vcur+VO(224)));
      wg_commit();
      wg_wait<1>(); pinu(s1);
      sm_unit<0>(s1,p0);
      sm_unit<1>(s1,p1);
      wg_fence();
      mma_pv(o1,p0,KD(vcur+VO(128)));
      mma_pv(o1,p1,KD(vcur+VO(160)));
      wg_commit();
      wg_wait<1>();
      sm_unit<2>(s1,p2);
      sm_unit<3>(s1,p3);
      wg_fence();
      mma_qk(s1,q1,KD(kcur+256));
      mma_pv(o1,p2,KD(vcur+VO(192)));
      mma_pv(o1,p3,KD(vcur+VO(224)));
      wg_commit();
      wg_wait<1>(); pinu(s0);
      sm_unit<0>(s0,p0);
      sm_unit<1>(s0,p1);
      wg_fence();
      mma_pv(o0,p0,KD(vcur+VO(384)));
      mma_pv(o0,p1,KD(vcur+VO(416)));
      wg_commit();
      wg_wait<1>();
      sm_unit<2>(s0,p2);
      sm_unit<3>(s0,p3);
      if (!(EXP & 16)) mbar_wait(kvfull+8*(sA+1), ph);
      wg_fence();
      mma_qk(s0,q0,KD(kcur+512));
      mma_pv(o0,p2,KD(vcur+VO(448)));
      mma_pv(o0,p3,KD(vcur+VO(480)));
      wg_commit();
      wg_wait<1>(); pinu(s1);
      sm_unit<0>(s1,p0);
      sm_unit<1>(s1,p1);
      wg_fence();
      mma_pv(o1,p0,KD(vcur+VO(384)));
      mma_pv(o1,p1,KD(vcur+VO(416)));
      wg_commit();
      wg_wait<1>();
      sm_unit<2>(s1,p2);
      sm_unit<3>(s1,p3);
      wg_fence();
      mma_qk(s1,q1,KD(kcur+512));
      mma_pv(o1,p2,KD(vcur+VO(448)));
      mma_pv(o1,p3,KD(vcur+VO(480)));
      wg_commit();
      wg_wait<1>(); pinu(s0);
      sm_unit<0>(s0,p0);
      sm_unit<1>(s0,p1);
      wg_fence();
      mma_pv(o0,p0,KD(vcur+VO(640)));
      mma_pv(o0,p1,KD(vcur+VO(672)));
      wg_commit();
      wg_wait<1>();
      if (!(EXP & 32) && lane==0) mbar_arrive(kvempty+8*sA);
      sm_unit<2>(s0,p2);
      sm_unit<3>(s0,p3);
      wg_fence();
      mma_qk(s0,q0,KD(kcur+768));
      mma_pv(o0,p2,KD(vcur+VO(704)));
      mma_pv(o0,p3,KD(vcur+VO(736)));
      wg_commit();
      wg_wait<1>(); pinu(s1);
      sm_unit<0>(s1,p0);
      sm_unit<1>(s1,p1);
      wg_fence();
      mma_pv(o1,p0,KD(vcur+VO(640)));
      mma_pv(o1,p1,KD(vcur+VO(672)));
      wg_commit();
      wg_wait<1>();
      sm_unit<2>(s1,p2);
      sm_unit<3>(s1,p3);
      wg_fence();
      mma_qk(s1,q1,KD(kcur+768));
      mma_pv(o1,p2,KD(vcur+VO(704)));
      mma_pv(o1,p3,KD(vcur+VO(736)));
      wg_commit();
      wg_wait<1>(); pinu(s0);
      sm_unit<0>(s0,p0);
      sm_unit<1>(s0,p1);
      wg_fence();
      mma_pv(o0,p0,KD(vcur+VO(896)));
      mma_pv(o0,p1,KD(vcur+VO(928)));
      wg_commit();
      wg_wait<1>();
      sm_unit<2>(s0,p2);
      sm_unit<3>(s0,p3);
      if (!(EXP & 16)) mbar_wait(kvfull+8*(sA^2), phn);
      wg_fence();
      mma_qk(s0,q0,KD(knxt));
      mma_pv(o0,p2,KD(vcur+VO(960)));
      mma_pv(o0,p3,KD(vcur+VO(992)));
      wg_commit();
      wg_wait<1>(); pinu(s1);
      sm_unit<0>(s1,p0);
      sm_unit<1>(s1,p1);
      wg_fence();
      mma_pv(o1,p0,KD(vcur+VO(896)));
      mma_pv(o1,p1,KD(vcur+VO(928)));
      wg_commit();
      wg_wait<1>();
      sm_unit<2>(s1,p2);
      sm_unit<3>(s1,p3);
      wg_wait<0>(); pinu(s0); pinu(o0); pinu(o1);
      flush(a1, o1);
      vprev = vcur;
    }
    wg_fence();
    mma_pv0(o1,p2,KD(vprev+VO(960)));
    mma_pv(o1,p3,KD(vprev+VO(992)));
    wg_commit(); flush(a0, o0); wg_wait<0>(); pinu(o1);
    if (lane == 0) mbar_arrive(kvempty + 8 * 3);
    flush(a1, o1);
  }
}

__device__ __forceinline__ void mma16816(float* d, const uint32_t (&a)[4], uint32_t b0, uint32_t b1) {
  asm("mma.sync.aligned.m16n8k16.row.col.f32.bf16.bf16.f32 {%0,%1,%2,%3}, {%4,%5,%6,%7}, {%8,%9}, {%0,%1,%2,%3};"
      : "+f"(d[0]), "+f"(d[1]), "+f"(d[2]), "+f"(d[3]) : "r"(a[0]), "r"(a[1]), "r"(a[2]), "r"(a[3]), "r"(b0), "r"(b1));
}
__device__ __forceinline__ uint32_t trans8(uint32_t a) { uint32_t r; asm("movmatrix.sync.aligned.m8n8.trans.b16 %0, %1;" : "=r"(r) : "r"(a)); return r; }
__device__ __forceinline__ void attn_online(const uint32_t (&qn)[4], float g0, float g1, uint8_t* dst, int pass, int lane) {
  uint32_t q[4];
#pragma unroll
  for (int i = 0; i < 4; i++) {
    const int src = (lane & ~3) | ((2 * lane + (i >> 1)) & 3);
    const uint32_t u = __shfl_sync(~0u, qn[i & 1], src), v = __shfl_sync(~0u, qn[2 + (i & 1)], src);
    q[i] = (lane & 2) ? v : u;
  }
  float o[12] = {};
  float m0 = -3e38f, m1 = -3e38f;
#pragma unroll 2
  for (int b = 0; b < 128; b++) {
    const uint4 k = __ldcg(g_kvb + b * 64 + lane), v = __ldcg(g_kvb + b * 64 + 32 + lane);
    float s[8] = {};
    mma16816(s, q, k.x, k.z); mma16816(s + 4, q, k.y, k.w);
    float x = fmaxf(fmaxf(m0, fmaxf(s[0], s[1])), fmaxf(s[4], s[5])), y = fmaxf(fmaxf(m1, fmaxf(s[2], s[3])), fmaxf(s[6], s[7]));
    x = fmaxf(x, __shfl_xor_sync(~0u, x, 1)); x = fmaxf(x, __shfl_xor_sync(~0u, x, 2));
    y = fmaxf(y, __shfl_xor_sync(~0u, y, 1)); y = fmaxf(y, __shfl_xor_sync(~0u, y, 2));
    const float cx = ex2((m0 - x) * QS), cy = ex2((m1 - y) * QS);
    m0 = x; m1 = y;
#pragma unroll
    for (int j = 0; j < 3; j++) { o[4 * j] *= cx; o[4 * j + 1] *= cx; o[4 * j + 2] *= cy; o[4 * j + 3] *= cy; }
    const uint32_t p[4] = {pack2(ex2((s[0] - x) * QS), ex2((s[1] - x) * QS)), pack2(ex2((s[2] - y) * QS), ex2((s[3] - y) * QS)),
                           pack2(ex2((s[4] - x) * QS), ex2((s[5] - x) * QS)), pack2(ex2((s[6] - y) * QS), ex2((s[7] - y) * QS))};
    mma16816(o, p, trans8(v.x), trans8(v.y)); mma16816(o + 4, p, trans8(v.z), trans8(v.w)); mma16816(o + 8, p, 0x3F803F80u, 0x3F803F80u);
  }
  const float a = __fdividef(g0, o[8]), b = __fdividef(g1, o[10]);
  const uint32_t w0 = pack2(o[0] * a, o[1] * a), w1 = pack2(o[2] * b, o[3] * b), w2 = pack2(o[4] * a, o[5] * a), w3 = pack2(o[6] * b, o[7] * b);
  if (pass == 0) {
    dst += (lane & 2) * 508 + (lane & 1) * 4;
    stg64(dst, w0, w2); stg64(dst + 128, w1, w3);
  } else {
    dst += (lane & 1) * 16 - (lane & 2) * 12;
    st_rlx64(dst, ~w0, ~w1); st_rlx64(dst + 16, ~w2, ~w3);
  }
}

__device__ __forceinline__ void store_o(const float (&o)[12], float g0, float g1, uint8_t* dst, int pass) {
  const float a = __fdividef(g0, o[8]), b = __fdividef(g1, o[10]);
  const uint32_t w0 = pack2(o[0] * a, o[1] * a), w1 = pack2(o[2] * b, o[3] * b), w2 = pack2(o[4] * a, o[5] * a), w3 = pack2(o[6] * b, o[7] * b);
  if (pass == 0) { stg32(dst, w0); stg32(dst + 128, w1); stg32(dst + 1024, w2); stg32(dst + 1152, w3); }
  else st_rlx128(dst, ~w0, ~w1, ~w2, ~w3);
}

__device__ __forceinline__ void attn_passes(uint32_t (&qh)[4][4], uint32_t (&qb)[4][4], float qn, uint8_t* odst, int wg, uint32_t (&r)[8][4], const uint8_t* src) {
  const int lane = threadIdx.x & 31;
  float g0 = 0.f, g1 = 0.f;
#pragma unroll 1
  for (int p = 0; p < 2; p++) {
    {
      uint32_t a0[6] = {}, a1[6] = {};
      attn_fast(qh[0], qh[1], a0, a1, lane);
      {
        uint32_t go;
        asm volatile("{\n.reg .pred p;\nmbarrier.test_wait.parity.shared::cta.b64 p, [%1], 0;\nselp.u32 %0, 1, 0, p;\n}" : "=r"(go) : "r"(sb + B_TAIL) : "memory");
#pragma unroll
        for (int j = 0; j < 8; j++) ld_rlx128(r[j], src + j * 512, PRE && go);
      }
      if (p == 0) {
        mbar_wait(sb + B_GREADY, 0);
        const uint32_t ga = sb + G_OFF + ((threadIdx.x >> 5) * 16 + (lane >> 2)) * 8;
        g0 = __uint_as_float(lds32(ga)); g1 = __uint_as_float(lds32(ga + 64));
        const float kn = __uint_as_float(lds32(sb + MISC_OFF + 32));
        qn = !FORCE_SLOW && qn * kn <= 372.f && qn <= 65536.f && kn <= 65536.f ? 128.f : NAN;
      }
      float o0[12], o1[12], hi = 0.f;
#pragma unroll
      for (int i = 0; i < 6; i++) { unpackh(a0[i], o0[2 * i], o0[2 * i + 1]); unpackh(a1[i], o1[2 * i], o1[2 * i + 1]); }
      const float lo = fminf(fminf(o0[8], o0[10]), fminf(o1[8], o1[10]));
#pragma unroll
      for (int i = 0; i < 11; i++) hi += fabsf(o0[i]) + fabsf(o1[i]);
      const bool ok = lo >= qn && hi < INFINITY;
      if (__all_sync(~0u, ok)) {
        store_o(o0, g0, g1, odst, p);
        store_o(o1, g0, g1, odst + 2048, p);
      } else {
#pragma unroll 1
        for (int h = 0; h < 2; h++) {
          attn_online(qb[0], g0, g1, odst + h * 2048, p, lane);
#pragma unroll
          for (int i = 0; i < 4; i++) qb[0][i] = qb[1][i];
        }
      }
    }
    if (p == 0) {
      odst += 32768 + (threadIdx.x & 96) * 8 + lane * 12;
      st_rlx128(odst, 0, 0, 0, 0); st_rlx128(odst + 2048, 0, 0, 0, 0);
      __syncwarp();
      if (lane == 0) mbar_arrive(sb + B_PUB + 32);
    }
#pragma unroll
    for (int i = 0; i < 4; i++) { qh[0][i] = qh[2][i]; qh[1][i] = qh[3][i]; qb[0][i] = qb[2][i]; qb[1][i] = qb[3][i]; }
  }
}

__device__ __forceinline__ uint32_t o_off(int c) { return sb + (c >> 1) * FST + (c & 1) * 4096; }
__device__ __forceinline__ void o_push(int c, int lane) {
  asm volatile("fence.proxy.async.shared::cta;" ::: "memory");
  __syncwarp();
  if (lane == 0) {
    uint32_t old;
    asm volatile("atom.shared.or.b32 %0, [%1], %2;" : "=r"(old) : "r"(sb + MISC_OFF + 40), "r"(1u << c) : "memory");
    if (!(old >> c & 1)) {
      const int pos = __popc(old);
      sts32(sb + MISC_OFF + 4 * pos, dlo(o_off(c), 1024));
      mbar_arrive(sb + B_Q + 8 * pos);
    }
  }
}

__device__ __forceinline__ float geglu(float x, float u, float c) {
  const float y = x * fmaf(x * x, 0.044715f * 0.7978845608028654f, 0.7978845608028654f);
  float t; asm("tanh.approx.f32 %0, %1;" : "=f"(t) : "f"(y));
  const float h = x * u * c;
  return fmaf(h, t, h);
}
__device__ __forceinline__ void store_h(const float (&d)[64], float c0, float c1, uint8_t* dst) {
#pragma unroll
  for (int j = 0; j < 8; j++) {
    stg32(dst + j * 1024, pack2(geglu(d[4 * j], d[32 + 4 * j], c0), geglu(d[4 * j + 1], d[33 + 4 * j], c0)));
    stg32(dst + j * 1024 + 128, pack2(geglu(d[4 * j + 2], d[34 + 4 * j], c1), geglu(d[4 * j + 3], d[35 + 4 * j], c1)));
  }
}

__global__ void __launch_bounds__(512, 1)
fused_kernel(const __grid_constant__ Maps mp, const uint16_t* __restrict__ gate_w, const uint4* __restrict__ wk, const uint4* __restrict__ wv,
             const uint8_t* __restrict__ wd_raw, const uint8_t* __restrict__ wo_raw, uint4* __restrict__ out) {
  extern __shared__ __align__(1024) uint8_t smem[];
  const int tid = threadIdx.x, lane = tid & 31;
  const int warp = __shfl_sync(~0u, tid >> 5, 0);
  const int wg = warp >> 2, wq4 = warp & 3;
  const int tb = blockIdx.x >> 3, cg = blockIdx.x & 7;
  const int half = cg & 1;

  if (warp == 12) {
    if (lane == 0) {
      EV(0);
      if ((uint32_t)__cvta_generic_to_shared(smem) != sb) __trap();
      for (int i = 0; i < 8; i++) mbar_init(sb + B_XFULL + 8 * i, 1);
      for (int i = 0; i < 4; i++) mbar_init(sb + B_WQ + 8 * i, 1);
      asm volatile("fence.mbarrier_init.release.cluster;" ::: "memory");
    }
    __syncwarp();
    const uint32_t xb = sb + B_XFULL + 32 * half, xd = sb + X_OFF + half * 65536;
    const int row = tb * 128 + half * 64;
    if (cg < 4) {
#pragma unroll
      for (int j = 0; j < 4; j++) u_tma3d(xb + 8 * j, 16384, xd + j * 16384, &mp.x, 0, row, 2 * j);
    }
#pragma unroll
    for (int j = 0; j < 4; j++) {
      u_tma2d(sb + B_WQ + 8 * j, 16384, sb + W_OFF + j * 16384, &mp.wq, cg * 64, j * 128);
      u_tma3d((xb ^ 32) + 8 * j, 16384, (xd ^ 65536) + j * 16384, &mp.x, 0, row ^ 64, 2 * j);
      if (cg >= 4) u_tma3d(xb + 8 * j, 16384, xd + j * 16384, &mp.x, 0, row, 2 * j);
    }
  } else if (tid == 416) {
    mbar_init(sb + B_GREADY, 1); mbar_init(sb + B_FFN1, 4);
    for (int i = 0; i < 4; i++) { mbar_init(sb + B_WFULL + 8 * i, 1); mbar_init(sb + B_WEMPTY + 8 * i, 8); mbar_init(sb + B_KVFULL + 8 * i, 1); mbar_init(sb + B_KVEMPTY + 8 * i, 8); mbar_init(sb + B_PUB + 8 * i, 4); }
    mbar_init(sb + B_PUB + 32, 8);
    for (int i = 0; i < 8; i++) { mbar_init(sb + B_FFULL + 8 * i, 2); mbar_init(sb + B_FEMPTY + 8 * i, 4); mbar_init(sb + B_Q + 8 * i, 1); }
    mbar_init(sb + B_TAIL, 4); sts32(sb + MISC_OFF + 40, 0);
    asm volatile("fence.mbarrier_init.release.cluster;" ::: "memory");
  } else if (tid == 448) {
    asm volatile("prefetch.tensormap [%0];" ::"l"(&mp.wg) : "memory");
    asm volatile("prefetch.tensormap [%0];" ::"l"(&mp.wu) : "memory");
    asm volatile("prefetch.tensormap [%0];" ::"l"(&mp.wd) : "memory");
    asm volatile("prefetch.tensormap [%0];" ::"l"(&mp.wo) : "memory");
    asm volatile("prefetch.tensormap [%0];" ::"l"(&mp.out) : "memory");
  }
  uint4 wa[4], wb[4];
  uint32_t wz[4];
  if (cg < 4 && wg == 2) {
    const uint4* w = (cg < 2 ? wk : wv) + (tid & 127) * 2;
#pragma unroll
    for (int i = 0; i < 4; i++) { wa[i] = __ldg(w + i * 256); wb[i] = __ldg(w + i * 256 + 1); wz[i] = __ldg(gate_w + (tid & 127) + i * 128); }
  }
  if (tid < 128) { sts32(sb + ONES_OFF + tid * 4, 0x3C003C00u); asm volatile("fence.proxy.async.shared::cta;" ::: "memory"); }
  __syncthreads();
  if (tid == 0) EV(1);

  uint8_t* const a_tb = g_a + (size_t)(tb * 2) * A_BYTES;
  uint32_t* const fl_tb = g_flags + 64 + tb * 128;

  if (wg == 3) {
    asm volatile("setmaxnreg.dec.sync.aligned.u32 %0;" ::"n"(REG_PROD));
    if (wq4 == 0) {
#pragma unroll 1
      for (int n = 0; n < 32; n++) {
        const int s = n & 3;
        const int hc = n < 24 ? (n & 24) + cg : 24 + (cg >> 1);
        mbar_wait_sleep<NS_W>(sb + B_WEMPTY + 8 * s, (n >> 2) & 1);
        u_tma2d_pair(sb + B_WFULL + 8 * s, sb + W_OFF + s * 16384, &mp.wg, &mp.wu, hc * 64, (n & 7) * 64, (n & 7) * 64);
        if (n == 8) { u_prefetch(wd_raw + blockIdx.x * 14336, 14336); u_prefetch(wo_raw + blockIdx.x * 4096, 4096); }
      }
      mbar_wait_sleep<NS_W>(sb + B_FFN1, 0);
#pragma unroll 1
      for (int n = 0; n < 36; n++) {
        const int s = n & 7;
        mbar_wait_sleep<NS_W>(sb + B_FEMPTY + 8 * s, ((n >> 3) & 1) ^ 1);
        u_tma4d(sb + B_FFULL + 8 * s, 16384, sb + s * FST + 8192, n < 28 ? &mp.wd : &mp.wo, n & 32, n < 28 ? 2 * n : 2 * (n & 3), cg & 6);
        if (n >= 32 && lane == 0) mbar_arrive(sb + B_FFULL + 8 * s);
      }
    } else if (wq4 == 1) {
      if (cg < 4) asm volatile("bar.sync 4, 192;" ::: "memory");
      uint32_t todo = 0x55555555u ^ (1u << 2 * tb), rdy = 0;
#pragma unroll 1
      for (int n = 1; n < 33; n++) {
        if (n == 15 ? rdy != 0x55555555u : !(rdy & todo)) {
          for (int i = 0; n == 15 ? rdy != 0x55555555u : !(rdy & todo); i++) {
            const uint64_t f = ld_acq64(g_flags + 2 * lane);
            rdy = __ballot_sync(~0u, (uint32_t)f & (uint32_t)(f >> 32) & 1);
            rdy &= (rdy >> 1) & 0x55555555u;
            if (i > 0x100000) __trap();
          }
          fence_async_gl();
        }
        const int c = __ffs(rdy & todo) - 1, s = n & 3;
        todo ^= 1u << c;
        if (!todo) todo = 0x55555555u;
        mbar_wait_sleep<NS_KV>(sb + B_KVEMPTY + 8 * s, ((n >> 2) & 1) ^ 1);
        u_bulk(sb + B_KVFULL + 8 * s, 8192, sb + KV_OFF + s * 8192, g_kv + c * 4096);
      }
    } else if (wq4 == 3) {
      if (cg < 4) {
        uint32_t* const fl = g_flags + (tb * 2 + half) * 2 + (cg >> 1);
        asm volatile("bar.sync 4, 192;" ::: "memory");
        fence_gpu();
        if (lane == 0) { st_rlx(fl, 1); EV(2); }
        asm volatile("bar.sync 5, 160;" ::: "memory");
        const uint32_t m = __reduce_max_sync(~0u, lds32(sb + MISC_OFF + 48 + (lane & 3) * 4));
        fence_gpu();
        if (lane == 0) st_rlx(fl, m | 3);
      }
#pragma unroll 1
      for (int e = 0; e < 5; e++) {
        mbar_wait_sleep<NS_W>(sb + B_PUB + 8 * e, 0);
        fence_gpu();
        const int idx = e < 3 ? 2 * (e * 8 + cg) : e == 3 ? 2 * (24 + (cg >> 1)) : 2 * cg + 1;
        if (lane < 2 && (e != 3 || lane == half)) st_rlx(fl_tb + lane * 64 + idx, 1);
      }
    } else {
      {
        mbar_wait_sleep<NS_W>(sb + B_KVEMPTY + 8 * GSL, 0);
        uint64_t f;
        for (int i = 0;; i++) {
          f = ld_acq64(g_flags + 2 * lane);
          if (__all_sync(~0u, (uint32_t)f & (uint32_t)(f >> 32) & 2)) break;
          if (i > 0x100000) __trap();
          __nanosleep(NS_F);
        }
        fence_async_gl();
        const uint32_t fk = __reduce_max_sync(~0u, max((uint32_t)f, (uint32_t)(f >> 32)));
        if (lane == 0) sts32(sb + MISC_OFF + 32, fk);
        __syncwarp();
        u_bulk(sb + B_GREADY, 1024, sb + G_OFF, g_gate + tb * 128);
      }
      mbar_wait_sleep<NS_W>(sb + B_FFN1, 0);
      const uint32_t* fl = fl_tb + half * 64 + 2 * lane;
      const uint8_t* src = a_tb + half * A_BYTES;
      int ready = 0;
#pragma unroll 1
      for (int n = 0; n < 32; n++) {
        if (n >= ready) {
          for (int i = 0;; i++) {
            const uint64_t f = ld_acq64(fl);
            const uint32_t rh = __ballot_sync(~0u, (uint32_t)f != 0), ro = __ballot_sync(~0u, (f >> 32) != 0);
            ready = __ffs(~rh) - 1;
            if (ready == 28) ready += (__ffs(~ro) - 1) >> 1;
            if (n < ready) break;
            if (i > 0x100000) __trap();
            __nanosleep(NS_F);
          }
          fence_async_gl();
        }
        const int s = n & 7;
        mbar_wait_sleep<NS_W>(sb + B_FEMPTY + 8 * s, ((n >> 3) & 1) ^ 1);
        u_bulk(sb + B_FFULL + 8 * s, 8192, sb + s * FST, src + n * 8192);
      }
      if (cg < 4) for (int i = 0; i < 4; i++) g_kv0[tb * 512 + cg * 128 + i * 32 + lane] = make_uint4(0, 0, 0, 0);
      uint32_t last = 0;
      if (lane == 0) { __threadfence(); last = atomicAdd(&g_done, 1) == gridDim.x - 1; __threadfence(); }
      if (__shfl_sync(~0u, last, 0)) {
        for (int i = lane; i < (64 + 32 * 64) / 4; i += 32) reinterpret_cast<uint4*>(g_flags)[i] = make_uint4(0, 0, 0, 0);
        if (lane == 0) g_done = 0;
      }
    }
  } else if (wg == 2) {
    asm volatile("setmaxnreg.inc.sync.aligned.u32 %0;" ::"n"(REG_GEMM));
    constexpr uint32_t H128 = dhi(1024, 1);
    float e[11] = {};
    if (cg < 4) {
#pragma unroll
      for (int i = 0; i < 4; i++) {
        const uint32_t a = sb + KV_OFF + i * 4096 + (tid & 127) * 32 + (tid & 4) * 4;
        sts128(a, wa[i].x, wa[i].z, wb[i].x, wb[i].z); sts128(a ^ 16, wa[i].y, wa[i].w, wb[i].y, wb[i].w); sts32(a + 16384, wz[i]);
      }
      asm volatile("fence.proxy.async.shared::cta;" ::: "memory");
      float d[12];
      zero(d);
      bar_sync(3);
      const uint32_t xl = dlo(sb + X_OFF + half * 65536, 16), wl = dlo(sb + KV_OFF, 16384);
#pragma unroll 1
      for (int j = 0; j < 4; j++) {
        mbar_wait(sb + B_XFULL + 32 * half + 8 * j, 0);
        wg_fence();
#pragma unroll
        for (int k = 0; k < 8; k++) mma_ss_t24(d, mk64(xl + j * 1024 + (k >> 2) * 512 + 2 * (k & 3), H128), KD(wl + j * 256 + 32 * k), 1);
        wg_commit();
      }
      wg_wait<0>(); pin(d);
      if ((tid & 127) == 0) EV(46);
      const float sc = cg < 2 ? 0.0625f : 1.f;
      const uint32_t w0 = packh(d[0] * sc, d[1] * sc), w1 = packh(d[4] * sc, d[5] * sc), w2 = packh(d[2] * sc, d[3] * sc), w3 = packh(d[6] * sc, d[7] * sc);
      st_rlx128(g_kv0 + tb * 512 + cg * 128 + (tid & 127), ~w0, ~w1, ~w2, ~w3);
      uint8_t* dst = g_kv + (tb * 2 + half) * 4096 + (cg >> 1) * 2048 + wq4 * 512 + ((lane * 8) ^ (lane & 16));
      stg64(dst, w0, w1); stg64(dst + 256, w2, w3);
      asm volatile("bar.arrive 4, 192;" ::: "memory");
      if ((tid & 127) == 0) EV(47);
#pragma unroll
      for (int i = 0; i < 11; i++) asm volatile("mov.b32 %0, %1;" : "=f"(e[i]) : "f"(d[i]));
    }
    {
      uint32_t r[4][4], pend = 15;
#pragma unroll 1
      for (int i = 0; pend && i < 0x100000; i++) {
#pragma unroll
        for (int j = 0; j < 4; j++) if (pend >> j & 1) ld_rlx128(r[j], g_kv0 + tb * 512 + j * 128 + (tid & 127), 1);
#pragma unroll
        for (int j = 0; j < 4; j++) if (__all_sync(~0u, min(min(r[j][0], r[j][1]), min(r[j][2], r[j][3])) != 0)) pend &= ~(1u << j);
      }
      if (cg < 4) bar_sync(3);
      const uint32_t a = sb + KV_OFF + wq4 * 512 + ((lane * 8) ^ (lane & 16));
#pragma unroll
      for (int j = 0; j < 4; j++) { sts64(a + (j & 1) * 4096 + (j >> 1) * 2048, ~r[j][0], ~r[j][1]); sts64(a + (j & 1) * 4096 + (j >> 1) * 2048 + 256, ~r[j][2], ~r[j][3]); }
      asm volatile("fence.proxy.async.shared::cta;" ::: "memory");
      bar_sync(3);
      if (tid == 256) { mbar_arrive(sb + B_KVFULL); EV(45); }
    }
    if (cg < 4) {
      g_kvb[(tb * 8 + half * 4 + wq4) * 64 + (cg >> 1) * 32 + lane] = make_uint4(pack2(e[0], e[1]), pack2(e[2], e[3]), pack2(e[4], e[5]), pack2(e[6], e[7]));
      uint32_t mx;
      if (cg < 2) {
        const float z0 = __shfl_sync(~0u, e[8], (lane & 7) * 4), z1 = __shfl_sync(~0u, e[10], (lane & 7) * 4);
        const float g = 1.f / (1.f + __expf((lane & 8) ? -z1 : -z0));
        if (lane < 16) g_gate[tb * 128 + half * 64 + wq4 * 16 + lane] = make_float2(g, 0.5f * (1.f - g));
        float n0 = sq4(e[0], e[1], e[4], e[5]), n1 = sq4(e[2], e[3], e[6], e[7]);
        n0 += __shfl_xor_sync(~0u, n0, 1); n1 += __shfl_xor_sync(~0u, n1, 1);
        n0 += __shfl_xor_sync(~0u, n0, 2); n1 += __shfl_xor_sync(~0u, n1, 2);
        mx = __reduce_max_sync(~0u, max(__float_as_uint(n0), __float_as_uint(n1)));
      } else {
        bool ok = true;
#pragma unroll
        for (int i = 0; i < 4; i++) {
          const int j = (i & 1) + (i >> 1) * 4;
          uint32_t c = max(__float_as_uint(e[j]) & 0x7fffffffu, __float_as_uint(e[j + 2]) & 0x7fffffffu);
          c = max(c, __shfl_xor_sync(~0u, c, 4)); c = max(c, __shfl_xor_sync(~0u, c, 8)); c = max(c, __shfl_xor_sync(~0u, c, 16));
          ok = ok && (c == 0 || (c >= 0x37800000u && c <= 0x47000000u));
        }
        mx = __all_sync(~0u, ok) ? 0 : 0x7f800001u;
      }
      if (lane == 0) sts32(sb + MISC_OFF + 48 + wq4 * 4, mx);
      asm volatile("bar.arrive 5, 160;" ::: "memory");
      if ((tid & 127) == 0) EV(52);
    }
    float d0[64], d1[64];
    zero(d0); zero(d1);
    if (QFIRST) mbar_wait(sb + B_WEMPTY + 24, 0);
    const uint32_t xl = dlo(sb + X_OFF, 16), wl = dlo(sb + W_OFF, 8192);
    uint8_t* const hdst = a_tb + wq4 * 256 + lane * 4;
    const uint32_t grow = sb + G_OFF + (wq4 * 16 + (lane >> 2)) * 8 + 4;
#pragma unroll 1
    for (int st = 0; st < 3; st++) {
#pragma unroll 1
      for (int kc = 0; kc < 8; kc++) {
        const int s = kc & 3;
        if (!QFIRST && st == 0) { mbar_wait(sb + B_XFULL + 8 * (kc >> 1), 0); mbar_wait(sb + B_XFULL + 32 + 8 * (kc >> 1), 0); }
        mbar_wait(sb + B_WFULL + 8 * s, (kc >> 2) & 1);
        const uint32_t a = xl + kc * 512, b = wl + s * 1024;
#pragma unroll
        for (int k = 0; k < 4; k++) {
          wg_fence();
          mma_ss_t128(d0, mk64(a + 2 * k, H128), mk64(b + 128 * k, H128), (kc | k) != 0);
          mma_ss_t128(d1, mk64(a + 4096 + 2 * k, H128), mk64(b + 128 * k, H128), (kc | k) != 0);
          wg_commit(); wg_wait<GW1>();
          if (GW1 && k == 0 && kc != 0 && lane == 0) mbar_arrive2(sb + B_WEMPTY + 8 * ((s + 3) & 3));
        }
        if (!GW1 && lane == 0) mbar_arrive2(sb + B_WEMPTY + 8 * s);
      }
      if (GW1) { wg_wait<0>(); if (lane == 0) mbar_arrive2(sb + B_WEMPTY + 8 * 3); }
      pin(d0); pin(d1);
      if (st == 0) { if (tid == 256) EV(8); mbar_wait(sb + B_GREADY, 0); }
      const int hc = st * 8 + cg;
      store_h(d0, __uint_as_float(lds32(grow)), __uint_as_float(lds32(grow + 64)), hdst + hc * 8192);
      store_h(d1, __uint_as_float(lds32(grow + 512)), __uint_as_float(lds32(grow + 576)), hdst + A_BYTES + hc * 8192);
      __syncwarp();
      if (lane == 0) mbar_arrive(sb + B_PUB + 8 * st);
      pin(d0); pin(d1);
    }
    {
#pragma unroll 1
      for (int kc = 0; kc < 8; kc++) {
        const int s = kc & 3;
        mbar_wait(sb + B_WFULL + 8 * s, (kc >> 2) & 1);
        const uint32_t a = xl + kc * 512 + half * 4096, b = wl + s * 1024;
#pragma unroll
        for (int k = 0; k < 4; k += 2) {
          wg_fence();
          mma_ss_t128(d0, mk64(a + 2 * k, H128), mk64(b + 128 * k, H128), (kc | k) != 0);
          mma_ss_t128(d0, mk64(a + 2 * k + 2, H128), mk64(b + 128 * k + 128, H128), 1);
          wg_commit(); wg_wait<GW1>();
          if (GW1 && k == 0 && kc != 0 && lane == 0) mbar_arrive2(sb + B_WEMPTY + 8 * ((s + 3) & 3));
        }
        if (!GW1 && lane == 0) mbar_arrive2(sb + B_WEMPTY + 8 * s);
      }
      wg_wait<0>();
      pin(d0);
      if (lane == 0) mbar_arrive(sb + B_FFN1);
      if (tid == 256) EV(12);
      const int hc = 24 + (cg >> 1);
      store_h(d0, __uint_as_float(lds32(grow + half * 512)), __uint_as_float(lds32(grow + half * 512 + 64)), hdst + half * A_BYTES + hc * 8192);
      __syncwarp();
      if (lane == 0) mbar_arrive(sb + B_PUB + 24);
      pin(d0);
    }
    const uint32_t al = dlo(sb, 1024), bl = dlo(sb + 8192, 8192);
    constexpr uint32_t HA = dhi(128, 0);
#pragma unroll 1
    for (int n = 0; n < 32 - NDEF; n++) {
      const int s = n & 7;
      mbar_wait_sleep<NS_G>(sb + B_FFULL + 8 * s, (n >> 3) & 1);
      const uint32_t a = al + s * (FST >> 4), b = bl + s * (FST >> 4);
#pragma unroll
      for (int k = 0; k < 4; k += FK) {
        wg_fence();
#pragma unroll
        for (int i = k; i < k + FK; i++) mma_ss_t128(d0, mk64(a + 128 * i, HA), mk64(b + 128 * i, H128), (n | i) != 0);
        wg_commit(); wg_wait<GW2>();
        if (GW2 && k == (GW2 - 1) * FK && n != 0 && lane == 0) mbar_arrive(sb + B_FEMPTY + 8 * ((s + 7) & 7));
      }
      if (!GW2 && lane == 0) mbar_arrive(sb + B_FEMPTY + 8 * s);
    }
    if (tid == 256) EV(18);
    wg_wait<0>();
    if (NDEF == 4 && lane == 0) mbar_arrive(sb + B_FEMPTY + 24);
#pragma unroll
    for (int s = 8 - NDEF; s < 8; s++) mbar_wait(sb + B_FFULL + 8 * s, 1);
    if (lane == 0) mbar_arrive(sb + B_TAIL);
#pragma unroll
    for (int s = 0; s < 4; s++) mbar_wait(sb + B_FFULL + 8 * s, 0);
    if (NDEF) {
      mbar_wait_sleep<NS_G>(sb + B_KVEMPTY + 24, 1);
      wg_fence();
#pragma unroll
      for (int k = 32 - 4 * NDEF; k < 32; k++) mma_ss_t128(d0, mk64(al + (k >> 2) * (FST >> 4) + 128 * (k & 3), HA), mk64(bl + (k >> 2) * (FST >> 4) + 128 * (k & 3), H128), 1);
      wg_commit();
    }
    if (tid == 256) EV(31);
#pragma unroll 1
    for (int n = 0; n < 8; n++) {
      mbar_wait(sb + B_Q + 8 * n, 0);
      const uint32_t a = lds32(sb + MISC_OFF + 4 * n);
      wg_fence();
      mma_ss_t128(d0, mk64(a, HA), mk64(a + (bl - al), H128), 1);
      mma_ss_t128(d0, mk64(a + 128, HA), mk64(a + (bl - al) + 128, H128), 1);
      wg_commit();
    }
    wg_wait<0>();
    pin(d0);
    if (tid == 256) EV(19);
    const uint32_t stg = sb + 4 * FST + wq4 * 256;
#pragma unroll
    for (int j = 0; j < 8; j++) {
      const int c = (2 * j + (lane >> 4)) & 7;
      stsm4(stg + (j >> 2) * FST + c * 1024 + ((lane & 15) ^ c) * 16, pack2(d0[8 * j], d0[8 * j + 1]), pack2(d0[8 * j + 2], d0[8 * j + 3]), pack2(d0[8 * j + 4], d0[8 * j + 5]), pack2(d0[8 * j + 6], d0[8 * j + 7]));
    }
    __syncwarp();
    uint4* const op = out + (tb * 128 + half * 64 + wq4 * 16 + (lane >> 4)) * 64 + (cg & 6) * 8 + (lane & 15);
#pragma unroll
    for (int j = 0; j < 8; j++) {
      uint4 v;
      asm volatile("ld.shared.v4.u32 {%0, %1, %2, %3}, [%4];" : "=r"(v.x), "=r"(v.y), "=r"(v.z), "=r"(v.w) : "r"(stg + ((lane >> 3) & 1) * FST + (lane & 7) * 1024 + ((2 * j + (lane >> 4)) ^ (lane & 7)) * 16) : "memory");
      op[j * 128] = v;
    }
    if (tid == 256) EV(20);
  } else {
    asm volatile("setmaxnreg.inc.sync.aligned.u32 %0;" ::"n"(REG_ATT));
    constexpr uint32_t H128 = dhi(1024, 1);
    const uint32_t xl = dlo(sb + X_OFF + wg * 65536, 16);
    uint32_t qh[4][4], qb[4][4];
    float qn;
    {
      float d[32];
      zero(d);
      const uint32_t wl = dlo(sb + W_OFF, 8192);
#pragma unroll 1
      for (int s = 0; s < 4; s++) {
        mbar_wait(sb + B_WQ + 8 * s, 0);
        mbar_wait(sb + B_XFULL + 32 * wg + 8 * s, 0);
        wg_fence();
#pragma unroll
        for (int k = 0; k < 8; k++) mma_ss_t64(d, mk64(xl + (2 * s + (k >> 2)) * 512 + 2 * (k & 3), H128), mk64(wl + s * 1024 + 128 * k, H128), 1);
        wg_commit();
        wg_wait<0>();
        if (lane == 0) mbar_arrive(sb + B_WEMPTY + 8 * s);
      }
      pin(d);
      if (tid == 0) EV(44);
      uint32_t nm = 0;
#pragma unroll
      for (int h = 0; h < 4; h++) {
        const float* dh = d + 8 * h;
#pragma unroll
        for (int i = 0; i < 4; i++) {
          const float c = (i & 1) ? QS / 32.f : QS * 16.f;
          qh[h][i] = packh(dh[2 * i] * c, dh[2 * i + 1] * c);
          qb[h][i] = pack2(dh[2 * i], dh[2 * i + 1]);
        }
        float n0 = sq4(dh[0], dh[1], dh[4], dh[5]), n1 = sq4(dh[2], dh[3], dh[6], dh[7]);
        n0 += __shfl_xor_sync(~0u, n0, 1); n1 += __shfl_xor_sync(~0u, n1, 1);
        n0 += __shfl_xor_sync(~0u, n0, 2); n1 += __shfl_xor_sync(~0u, n1, 2);
        nm = max(nm, max(__float_as_uint(n0), __float_as_uint(n1)));
      }
      qn = __uint_as_float(nm) * (QS * QS);
    }
    if (tid == 0) EV(3);
    mbar_wait(sb + B_KVFULL, 0);
    if (tid == 0) { EV(5); EVC(0); }
    uint8_t* odst = a_tb + wg * A_BYTES + (224 + cg * 4) * 1024 + wq4 * 256 + lane * 4;
    const uint8_t* src = a_tb + half * A_BYTES + 256 * 1024 + warp * 4096 + lane * 16;
    uint32_t r[8][4];
    attn_passes(qh, qb, qn, odst, wg, r, src);
    mbar_wait(sb + B_TAIL, 0);
    const uint32_t dst = o_off(warp) + (lane >> 4) * 1024 + (lane & 15) * 16;
    uint32_t pend = 255;
#pragma unroll 1
    for (int i = 0; i < 0x100000; i++) {
#pragma unroll
      for (int j = 0; j < 8; j++) if (__all_sync(~0u, min(min(r[j][0], r[j][1]), min(r[j][2], r[j][3])) != 0)) {
        stsm4(dst + (j >> 2) * 2048 + (j & 3) * 256, ~r[j][0], ~r[j][1], ~r[j][2], ~r[j][3]);
        pend ^= 1u << j;
      }
      if (!pend) break;
#pragma unroll
      for (int j = 0; j < 8; j++) ld_rlx128(r[j], src + j * 512, pend & (1u << j));
    }
    o_push(warp, lane);
  }
}

typedef CUresult (*EncodeFn)(CUtensorMap*, CUtensorMapDataType, cuuint32_t, void*, const cuuint64_t*, const cuuint64_t*, const cuuint32_t*, const cuuint32_t*,
                             CUtensorMapInterleave, CUtensorMapSwizzle, CUtensorMapL2promotion, CUtensorMapFloatOOBfill);

void make_map(EncodeFn fn, CUtensorMap* m, const void* p, uint64_t cols, uint64_t rows, uint32_t bc, uint32_t br, CUtensorMapSwizzle sw) {
  cuuint64_t dims[2] = {cols, rows}, strides[1] = {cols * 2};
  cuuint32_t box[2] = {bc, br}, es[2] = {1, 1};
  fn(m, CU_TENSOR_MAP_DATA_TYPE_BFLOAT16, 2, const_cast<void*>(p), dims, strides, box, es, CU_TENSOR_MAP_INTERLEAVE_NONE, sw,
     CU_TENSOR_MAP_L2_PROMOTION_L2_128B, CU_TENSOR_MAP_FLOAT_OOB_FILL_NONE);
}

void make_map3(EncodeFn fn, CUtensorMap* m, const void* p, uint64_t bw, uint64_t nblk, uint64_t rows, uint32_t bc, uint32_t br, CUtensorMapSwizzle sw) {
  cuuint64_t dims[3] = {bw, rows, nblk}, strides[2] = {bw * nblk * 2, bw * 2};
  cuuint32_t box[3] = {bc, br, 2}, es[3] = {1, 1, 1};
  fn(m, CU_TENSOR_MAP_DATA_TYPE_BFLOAT16, 3, const_cast<void*>(p), dims, strides, box, es, CU_TENSOR_MAP_INTERLEAVE_NONE, sw,
     CU_TENSOR_MAP_L2_PROMOTION_L2_128B, CU_TENSOR_MAP_FLOAT_OOB_FILL_NONE);
}

void make_map4(EncodeFn fn, CUtensorMap* m, const void* p, uint64_t rows, uint64_t rg) {
  cuuint64_t dims[4] = {64, rg, rows / rg, 8}, strides[3] = {1024, rg * 1024, 128};
  cuuint32_t box[4] = {64, 32, 2, 2}, es[4] = {1, 1, 1, 1};
  fn(m, CU_TENSOR_MAP_DATA_TYPE_BFLOAT16, 4, const_cast<void*>(p), dims, strides, box, es, CU_TENSOR_MAP_INTERLEAVE_NONE, CU_TENSOR_MAP_SWIZZLE_128B,
     CU_TENSOR_MAP_L2_PROMOTION_L2_128B, CU_TENSOR_MAP_FLOAT_OOB_FILL_NONE);
}

}

extern "C" void kernel_launch(void* const* d_in, const int* in_sizes, int n_in, void* d_out, int out_size) {
  void* fp = nullptr;
  cudaDriverEntryPointQueryResult qr;
  cudaGetDriverEntryPoint("cuTensorMapEncodeTiled", &fp, cudaEnableDefault, &qr);
  EncodeFn fn = (EncodeFn)fp;
  Maps mp;
  make_map3(fn, &mp.x, d_in[0], 64, 8, S_, 64, 64, CU_TENSOR_MAP_SWIZZLE_128B);
  make_map(fn, &mp.wq, d_in[1], D_, D_, 64, 128, CU_TENSOR_MAP_SWIZZLE_128B);
  make_map4(fn, &mp.wo, d_in[4], D_, 64);
  make_map(fn, &mp.wg, d_in[6], F_, D_, 64, 64, CU_TENSOR_MAP_SWIZZLE_128B);
  make_map(fn, &mp.wu, d_in[7], F_, D_, 64, 64, CU_TENSOR_MAP_SWIZZLE_128B);
  make_map4(fn, &mp.wd, d_in[8], F_, 32);
  make_map3(fn, &mp.out, d_out, 64, 8, S_, 64, 64, CU_TENSOR_MAP_SWIZZLE_128B);
  cudaFuncSetAttribute(fused_kernel, cudaFuncAttributeMaxDynamicSharedMemorySize, SMEM_BYTES);
  fused_kernel<<<128, 512, SMEM_BYTES, cudaStreamPerThread>>>(mp, (const uint16_t*)d_in[9], (const uint4*)d_in[2], (const uint4*)d_in[3], (const uint8_t*)d_in[8], (const uint8_t*)d_in[4], (uint4*)d_out);
}
```

```cpp
#include <cuda_runtime.h>
#include <cuda_bf16.h>
#include <cuda.h>
#include <stdint.h>

#define DEG 2
#define REG_ATT 160
#define REG_GEMM 160
#define REG_PROD 32
#define FORCE_SLOW 0
#define NS_W 100
#define NS_KV 200
#define NS_F 200
#define NS_G 50
#define GW1 0
#define HINT 4000
#define PW 0
#define PRE 1
#define GSL 1
#define QFIRST 1
#define HNP 200
#define S3K 4

namespace {

constexpr int S_ = 2048, D_ = 512, F_ = 1792;
constexpr float QS = 0.25f * 1.4426950408889634f;

constexpr uint32_t sb = 1024;
constexpr uint32_t X_OFF = 0;
constexpr uint32_t W_OFF = 131072;
constexpr uint32_t KV_OFF = 196608;
constexpr uint32_t ONES_OFF = 229376;
constexpr uint32_t G_OFF = 229888;
constexpr uint32_t MISC_OFF = 231552;
constexpr uint32_t BAR_OFF = 231616;
constexpr uint32_t B_XFULL = BAR_OFF;
constexpr uint32_t B_PUB = B_XFULL + 64;
constexpr uint32_t B_GREADY = B_XFULL + 128;
constexpr uint32_t B_FFN1 = B_GREADY + 8;
constexpr uint32_t B_WFULL = B_FFN1 + 8;
constexpr uint32_t B_WEMPTY = B_WFULL + 32;
constexpr uint32_t B_KVFULL = B_WEMPTY + 32;
constexpr uint32_t B_KVEMPTY = B_KVFULL + 32;
constexpr uint32_t B_FFULL = B_KVEMPTY + 32;
constexpr uint32_t B_FEMPTY = B_FFULL + 64;
constexpr uint32_t B_WQ = B_FEMPTY + 64;
constexpr uint32_t B_TAIL = B_WQ + 32;
constexpr uint32_t B_Q = B_TAIL + 8;
constexpr uint32_t SMEM_BYTES = B_Q + 64;
constexpr uint32_t FST = 24576;
static_assert(SMEM_BYTES <= 232448, "smem");

constexpr int A_BYTES = 288 * 1024;
__device__ __align__(1024) uint8_t g_kv[32 * 4096];
__device__ uint4 g_kv0[16 * 512];
__device__ uint4 g_kvb[128 * 64];
__device__ __align__(1024) float2 g_gate[S_];
__device__ __align__(1024) uint8_t g_a[32 * A_BYTES];
__device__ __align__(256) uint32_t g_flags[64 + 32 * 64];
__device__ uint32_t g_done;

#define EVW(i)
#define EV(i)
#define EVC(i)
struct Maps { CUtensorMap x, wq, wo, wg, wu, wd, wg2, wu2; };

__device__ __forceinline__ void wg_fence() { asm volatile("wgmma.fence.sync.aligned;" ::: "memory"); }
__device__ __forceinline__ void wg_commit() { asm volatile("wgmma.commit_group.sync.aligned;" ::: "memory"); }
template <int N> __device__ __forceinline__ void wg_wait() { asm volatile("wgmma.wait_group.sync.aligned %0;" ::"n"(N) : "memory"); }
template <int N> __device__ __forceinline__ void pin(float (&d)[N]) {
#pragma unroll
  for (int i = 0; i < N; i++) asm volatile("" : "+f"(d[i])::"memory");
}
template <int N> __device__ __forceinline__ void pinu(uint32_t (&d)[N]) {
#pragma unroll
  for (int i = 0; i < N; i++) asm volatile("" : "+r"(d[i])::"memory");
}
template <int N> __device__ __forceinline__ void zero(float (&d)[N]) {
#pragma unroll
  for (int i = 0; i < N; i++) d[i] = 0.f;
  pin(d);
}
__device__ __forceinline__ uint64_t mk64(uint32_t lo, uint32_t hi) { return ((uint64_t)hi << 32) | lo; }
__host__ __device__ constexpr uint32_t dhi(uint32_t sbo, uint32_t sw) { return (sbo >> 4) | (sw << 30); }
__device__ __forceinline__ uint32_t dlo(uint32_t addr, uint32_t lbo) { return (addr >> 4) | ((lbo >> 4) << 16); }

__device__ __forceinline__ void mbar_init(uint32_t b, uint32_t n) { asm volatile("mbarrier.init.shared::cta.b64 [%0], %1;" ::"r"(b), "r"(n) : "memory"); }
__device__ __forceinline__ void mbar_arrive(uint32_t b) { asm volatile("mbarrier.arrive.shared::cta.b64 _, [%0];" ::"r"(b) : "memory"); }
__device__ __forceinline__ void mbar_arrive2(uint32_t b) { asm volatile("mbarrier.arrive.shared::cta.b64 _, [%0], 2;" ::"r"(b) : "memory"); }
__device__ __forceinline__ void mbar_expect(uint32_t b, uint32_t bytes) { asm volatile("mbarrier.arrive.expect_tx.shared::cta.b64 _, [%0], %1;" ::"r"(b), "r"(bytes) : "memory"); }
__device__ __forceinline__ void mbar_wait(uint32_t b, uint32_t parity) {
  asm volatile(
      "{\n.reg .pred p;\n.reg .u32 c;\n"
      "mbarrier.try_wait.parity.shared::cta.b64 p, [%0], %1;\n"
      "@p bra DONE;\n"
      "mov.u32 c, 0;\n"
      "SPIN:\n"
      "mbarrier.try_wait.parity.shared::cta.b64 p, [%0], %1;\n"
      "@p bra DONE;\n"
      "add.u32 c, c, 1;\n"
      "setp.lt.u32 p, c, 0x100000;\n"
      "@p bra SPIN;\n"
      "trap;\n"
      "DONE:\n}\n" ::"r"(b), "r"(parity) : "memory");
}
template <int NS> __device__ __forceinline__ void mbar_wait_sleep(uint32_t b, uint32_t parity) {
  asm volatile(
      "{\n.reg .pred p;\n.reg .u32 c;\n"
      "mov.u32 c, 0;\n"
      "SPIN:\n"
      "mbarrier.try_wait.parity.shared::cta.b64 p, [%0], %1, %2;\n"
      "@p bra.uni DONE;\n"
      "add.u32 c, c, 1;\n"
      "setp.lt.u32 p, c, 0x40000;\n"
      "@p bra.uni SPIN;\n"
      "trap;\n"
      "DONE:\n}\n" ::"r"(b), "r"(parity), "n"(HINT) : "memory");
}
template <int NS> __device__ __forceinline__ void mbar_wait_ns(uint32_t b, uint32_t parity) {
  asm volatile(
      "{\n.reg .pred p;\n.reg .u32 c;\n"
      "mov.u32 c, 0;\n"
      "SPIN:\n"
      "mbarrier.test_wait.parity.shared::cta.b64 p, [%0], %1;\n"
      "@p bra.uni DONE;\n"
      "nanosleep.u32 %2;\n"
      "add.u32 c, c, 1;\n"
      "setp.lt.u32 p, c, 0x100000;\n"
      "@p bra.uni SPIN;\n"
      "trap;\n"
      "DONE:\n}\n" ::"r"(b), "r"(parity), "n"(NS) : "memory");
}
#define ELECT "{\n.reg .pred p;\nelect.sync _|p, 0xffffffff;\n@p mbarrier.arrive.expect_tx.shared::cta.b64 _, [%0], %1;\n"
__device__ __forceinline__ void u_tma3d(uint32_t bar, uint32_t bytes, uint32_t dst, const CUtensorMap* m, int c0, int c1, int c2) {
  asm volatile(ELECT "@p cp.async.bulk.tensor.3d.shared::cluster.global.mbarrier::complete_tx::bytes [%2], [%3, {%4, %5, %6}], [%0];\n}\n" ::"r"(bar), "r"(bytes), "r"(dst), "l"(m), "r"(c0), "r"(c1), "r"(c2) : "memory");
}
__device__ __forceinline__ void u_tma4d(uint32_t bar, uint32_t bytes, uint32_t dst, const CUtensorMap* m, int c1, int c2, int c3) {
  asm volatile(ELECT "@p cp.async.bulk.tensor.4d.shared::cluster.global.mbarrier::complete_tx::bytes [%2], [%3, {0, %4, %5, %6}], [%0];\n}\n" ::"r"(bar), "r"(bytes), "r"(dst), "l"(m), "r"(c1), "r"(c2), "r"(c3) : "memory");
}
__device__ __forceinline__ void u_tma2d(uint32_t bar, uint32_t bytes, uint32_t dst, const CUtensorMap* m, int c0, int c1) {
  asm volatile(ELECT "@p cp.async.bulk.tensor.2d.shared::cluster.global.mbarrier::complete_tx::bytes [%2], [%3, {%4, %5}], [%0];\n}\n" ::"r"(bar), "r"(bytes), "r"(dst), "l"(m), "r"(c0), "r"(c1) : "memory");
}
__device__ __forceinline__ void u_tma2d_pair(uint32_t bar, uint32_t dst, const CUtensorMap* m0, const CUtensorMap* m1, int c0, int c1, int c1b) {
  asm volatile(ELECT "@p cp.async.bulk.tensor.2d.shared::cluster.global.mbarrier::complete_tx::bytes [%2], [%3, {%5, %6}], [%0];\n"
               "@p cp.async.bulk.tensor.2d.shared::cluster.global.mbarrier::complete_tx::bytes [%2 + 8192], [%4, {%5, %7}], [%0];\n}\n" ::"r"(bar), "r"(16384), "r"(dst), "l"(m0), "l"(m1), "r"(c0), "r"(c1), "r"(c1b) : "memory");
}
__device__ __forceinline__ void u_bulk(uint32_t bar, uint32_t bytes, uint32_t dst, const void* src) {
  asm volatile(ELECT "@p cp.async.bulk.shared::cluster.global.mbarrier::complete_tx::bytes [%2], [%3], %1, [%0];\n}\n" ::"r"(bar), "r"(bytes), "r"(dst), "l"(src) : "memory");
}
__device__ __forceinline__ void u_prefetch(const void* src, uint32_t bytes) {
  asm volatile("{\n.reg .pred p;\nelect.sync _|p, 0xffffffff;\n@p cp.async.bulk.prefetch.L2.global [%0], %1;\n}\n" ::"l"(src), "r"(bytes) : "memory");
}
__device__ __forceinline__ void fence_gpu() { asm volatile("fence.acq_rel.gpu;" ::: "memory"); }
__device__ __forceinline__ void st_rlx(uint32_t* p, uint32_t v) { asm volatile("st.relaxed.gpu.global.u32 [%0], %1;" ::"l"(p), "r"(v) : "memory"); }
__device__ __forceinline__ void st_rlx64(void* p, uint32_t a, uint32_t b) { asm volatile("st.relaxed.gpu.global.v2.u32 [%0], {%1, %2};" ::"l"(p), "r"(a), "r"(b) : "memory"); }
__device__ __forceinline__ void st_rlx128(void* p, uint32_t a, uint32_t b, uint32_t c, uint32_t d) { asm volatile("st.relaxed.gpu.global.v4.u32 [%0], {%1, %2, %3, %4};" ::"l"(p), "r"(a), "r"(b), "r"(c), "r"(d) : "memory"); }
__device__ __forceinline__ void ld_rlx128(uint32_t (&v)[4], const void* p, uint32_t c) {
  asm volatile("{\n.reg .pred p;\nsetp.ne.u32 p, %5, 0;\nmov.u32 %0, 0;\nmov.u32 %1, 0;\nmov.u32 %2, 0;\nmov.u32 %3, 0;\n@p ld.relaxed.gpu.global.v4.u32 {%0, %1, %2, %3}, [%4];\n}" : "=r"(v[0]), "=r"(v[1]), "=r"(v[2]), "=r"(v[3]) : "l"(p), "r"(c) : "memory");
}
__device__ __forceinline__ uint64_t ld_acq64(const uint32_t* p) { uint64_t v; asm volatile("ld.acquire.gpu.global.u64 %0, [%1];" : "=l"(v) : "l"(p) : "memory"); return v; }
__device__ __forceinline__ void tma2d(uint32_t dst, const CUtensorMap* m, int c0, int c1, uint32_t bar) {
  asm volatile("cp.async.bulk.tensor.2d.shared::cluster.global.mbarrier::complete_tx::bytes [%0], [%1, {%3, %4}], [%2];" ::"r"(dst), "l"(m), "r"(bar), "r"(c0), "r"(c1) : "memory");
}
__device__ __forceinline__ void bulk_ld(uint32_t dst, const void* src, uint32_t bytes, uint32_t bar) {
  asm volatile("cp.async.bulk.shared::cluster.global.mbarrier::complete_tx::bytes [%0], [%1], %2, [%3];" ::"r"(dst), "l"(src), "r"(bytes), "r"(bar) : "memory");
}
__device__ __forceinline__ void l2_prefetch(const void* src, uint32_t bytes) {
  asm volatile("cp.async.bulk.prefetch.L2.global [%0], %1;" ::"l"(src), "r"(bytes) : "memory");
}
__device__ __forceinline__ uint32_t ld_acq(const uint32_t* p) { uint32_t v; asm volatile("ld.acquire.gpu.global.u32 %0, [%1];" : "=r"(v) : "l"(p) : "memory"); return v; }
__device__ __forceinline__ void st_rel(uint32_t* p, uint32_t v) { asm volatile("st.release.gpu.global.u32 [%0], %1;" ::"l"(p), "r"(v) : "memory"); }
__device__ __forceinline__ void fence_async_all() { asm volatile("fence.proxy.async;" ::: "memory"); }
__device__ __forceinline__ void fence_async_gl() { asm volatile("fence.proxy.async.global;" ::: "memory"); }
__device__ __forceinline__ void bar_sync(int id) { asm volatile("bar.sync %0, 128;" ::"r"(id) : "memory"); }
__device__ __forceinline__ uint32_t pack2(float lo, float hi) { uint32_t r; asm("cvt.rn.bf16x2.f32 %0, %1, %2;" : "=r"(r) : "f"(hi), "f"(lo)); return r; }
__device__ __forceinline__ float ex2(float a) { float r; asm("ex2.approx.ftz.f32 %0, %1;" : "=f"(r) : "f"(a)); return r; }
__device__ __forceinline__ float sq4(float a, float b, float c, float d) { return fmaf(a, a, b * b) + fmaf(c, c, d * d); }
__device__ __forceinline__ void stg32(void* p, uint32_t v) { asm volatile("st.global.u32 [%0], %1;" ::"l"(p), "r"(v) : "memory"); }
__device__ __forceinline__ void stg64(void* p, uint32_t a, uint32_t b) { asm volatile("st.global.v2.u32 [%0], {%1, %2};" ::"l"(p), "r"(a), "r"(b) : "memory"); }
__device__ __forceinline__ void sts128(uint32_t a, uint32_t x, uint32_t y, uint32_t z, uint32_t w) { asm volatile("st.shared.v4.u32 [%0], {%1, %2, %3, %4};" ::"r"(a), "r"(x), "r"(y), "r"(z), "r"(w) : "memory"); }
__device__ __forceinline__ void stsm4(uint32_t a, uint32_t x, uint32_t y, uint32_t z, uint32_t w) { asm volatile("stmatrix.sync.aligned.m8n8.x4.shared.b16 [%0], {%1,%2,%3,%4};" ::"r"(a), "r"(x), "r"(y), "r"(z), "r"(w) : "memory"); }
__device__ __forceinline__ void sts64(uint32_t a, uint32_t x, uint32_t y) { asm volatile("st.shared.v2.u32 [%0], {%1, %2};" ::"r"(a), "r"(x), "r"(y) : "memory"); }
__device__ __forceinline__ void sts32(uint32_t a, uint32_t v) { asm volatile("st.shared.u32 [%0], %1;" ::"r"(a), "r"(v) : "memory"); }
__device__ __forceinline__ uint32_t lds32(uint32_t a) { uint32_t v; asm volatile("ld.shared.u32 %0, [%1];" : "=r"(v) : "r"(a) : "memory"); return v; }

__device__ __forceinline__ void mma_qk(uint32_t (&d)[16], const uint32_t (&a)[4], uint64_t b) {
  asm volatile("{\n.reg .pred p;\nsetp.ne.b32 p, 0, 0;\n"
    "wgmma.mma_async.sync.aligned.m64n64k16.f16.f16.f16 {%0,%1,%2,%3,%4,%5,%6,%7,%8,%9,%10,%11,%12,%13,%14,%15}, {%16,%17,%18,%19}, %20, p, 1, 1, 0;\n}\n"
    : "+r"(d[0]),"+r"(d[1]),"+r"(d[2]),"+r"(d[3]),"+r"(d[4]),"+r"(d[5]),"+r"(d[6]),"+r"(d[7]),"+r"(d[8]),"+r"(d[9]),"+r"(d[10]),"+r"(d[11]),"+r"(d[12]),"+r"(d[13]),"+r"(d[14]),"+r"(d[15]) : "r"(a[0]),"r"(a[1]),"r"(a[2]),"r"(a[3]),"l"(b));
}
__device__ __forceinline__ void mma_pv(uint32_t (&d)[6], const uint32_t (&a)[4], uint64_t b) {
  asm volatile("{\n.reg .pred p;\nsetp.ne.b32 p, 1, 0;\n"
    "wgmma.mma_async.sync.aligned.m64n24k16.f16.f16.f16 {%0,%1,%2,%3,%4,%5}, {%6,%7,%8,%9}, %10, p, 1, 1, 1;\n}\n"
    : "+r"(d[0]),"+r"(d[1]),"+r"(d[2]),"+r"(d[3]),"+r"(d[4]),"+r"(d[5]) : "r"(a[0]),"r"(a[1]),"r"(a[2]),"r"(a[3]),"l"(b));
}
__device__ __forceinline__ void mma_pv0(uint32_t (&d)[6], const uint32_t (&a)[4], uint64_t b) {
  asm volatile("{\n.reg .pred p;\nsetp.ne.b32 p, 0, 0;\n"
    "wgmma.mma_async.sync.aligned.m64n24k16.f16.f16.f16 {%0,%1,%2,%3,%4,%5}, {%6,%7,%8,%9}, %10, p, 1, 1, 1;\n}\n"
    : "+r"(d[0]),"+r"(d[1]),"+r"(d[2]),"+r"(d[3]),"+r"(d[4]),"+r"(d[5]) : "r"(a[0]),"r"(a[1]),"r"(a[2]),"r"(a[3]),"l"(b));
}
__device__ __forceinline__ void mma_ss_t128(float (&d)[64], uint64_t a, uint64_t b, int acc) {
  asm volatile("{\n.reg .pred p;\nsetp.ne.b32 p, %66, 0;\n"
    "wgmma.mma_async.sync.aligned.m64n128k16.f32.bf16.bf16 {%0,%1,%2,%3,%4,%5,%6,%7,%8,%9,%10,%11,%12,%13,%14,%15,%16,%17,%18,%19,%20,%21,%22,%23,%24,%25,%26,%27,%28,%29,%30,%31,%32,%33,%34,%35,%36,%37,%38,%39,%40,%41,%42,%43,%44,%45,%46,%47,%48,%49,%50,%51,%52,%53,%54,%55,%56,%57,%58,%59,%60,%61,%62,%63}, %64, %65, p, 1, 1, 0, 1;\n}\n"
    : "+f"(d[0]),"+f"(d[1]),"+f"(d[2]),"+f"(d[3]),"+f"(d[4]),"+f"(d[5]),"+f"(d[6]),"+f"(d[7]),"+f"(d[8]),"+f"(d[9]),"+f"(d[10]),"+f"(d[11]),"+f"(d[12]),"+f"(d[13]),"+f"(d[14]),"+f"(d[15]),"+f"(d[16]),"+f"(d[17]),"+f"(d[18]),"+f"(d[19]),"+f"(d[20]),"+f"(d[21]),"+f"(d[22]),"+f"(d[23]),"+f"(d[24]),"+f"(d[25]),"+f"(d[26]),"+f"(d[27]),"+f"(d[28]),"+f"(d[29]),"+f"(d[30]),"+f"(d[31]),"+f"(d[32]),"+f"(d[33]),"+f"(d[34]),"+f"(d[35]),"+f"(d[36]),"+f"(d[37]),"+f"(d[38]),"+f"(d[39]),"+f"(d[40]),"+f"(d[41]),"+f"(d[42]),"+f"(d[43]),"+f"(d[44]),"+f"(d[45]),"+f"(d[46]),"+f"(d[47]),"+f"(d[48]),"+f"(d[49]),"+f"(d[50]),"+f"(d[51]),"+f"(d[52]),"+f"(d[53]),"+f"(d[54]),"+f"(d[55]),"+f"(d[56]),"+f"(d[57]),"+f"(d[58]),"+f"(d[59]),"+f"(d[60]),"+f"(d[61]),"+f"(d[62]),"+f"(d[63]) : "l"(a),"l"(b),"r"(acc));
}
__device__ __forceinline__ void mma_ss_t64(float (&d)[32], uint64_t a, uint64_t b, int acc) {
  asm volatile("{\n.reg .pred p;\nsetp.ne.b32 p, %34, 0;\n"
    "wgmma.mma_async.sync.aligned.m64n64k16.f32.bf16.bf16 {%0,%1,%2,%3,%4,%5,%6,%7,%8,%9,%10,%11,%12,%13,%14,%15,%16,%17,%18,%19,%20,%21,%22,%23,%24,%25,%26,%27,%28,%29,%30,%31}, %32, %33, p, 1, 1, 0, 1;\n}\n"
    : "+f"(d[0]),"+f"(d[1]),"+f"(d[2]),"+f"(d[3]),"+f"(d[4]),"+f"(d[5]),"+f"(d[6]),"+f"(d[7]),"+f"(d[8]),"+f"(d[9]),"+f"(d[10]),"+f"(d[11]),"+f"(d[12]),"+f"(d[13]),"+f"(d[14]),"+f"(d[15]),"+f"(d[16]),"+f"(d[17]),"+f"(d[18]),"+f"(d[19]),"+f"(d[20]),"+f"(d[21]),"+f"(d[22]),"+f"(d[23]),"+f"(d[24]),"+f"(d[25]),"+f"(d[26]),"+f"(d[27]),"+f"(d[28]),"+f"(d[29]),"+f"(d[30]),"+f"(d[31]) : "l"(a),"l"(b),"r"(acc));
}
__device__ __forceinline__ void mma_ss_t24(float (&d)[12], uint64_t a, uint64_t b, int acc) {
  asm volatile("{\n.reg .pred p;\nsetp.ne.b32 p, %14, 0;\n"
    "wgmma.mma_async.sync.aligned.m64n24k16.f32.bf16.bf16 {%0,%1,%2,%3,%4,%5,%6,%7,%8,%9,%10,%11}, %12, %13, p, 1, 1, 0, 1;\n}\n"
    : "+f"(d[0]),"+f"(d[1]),"+f"(d[2]),"+f"(d[3]),"+f"(d[4]),"+f"(d[5]),"+f"(d[6]),"+f"(d[7]),"+f"(d[8]),"+f"(d[9]),"+f"(d[10]),"+f"(d[11]) : "l"(a),"l"(b),"r"(acc));
}

__device__ __forceinline__ uint32_t hfma2(uint32_t a, uint32_t b, uint32_t c) { uint32_t r; asm("fma.rn.f16x2 %0, %1, %2, %3;" : "=r"(r) : "r"(a), "r"(b), "r"(c)); return r; }
__device__ __forceinline__ uint32_t packh(float lo, float hi) { uint32_t r; asm("cvt.rn.f16x2.f32 %0, %1, %2;" : "=r"(r) : "f"(hi), "f"(lo)); return r; }
__device__ __forceinline__ void unpackh(uint32_t a, float& lo, float& hi) { asm("{\n.reg .b16 l, h;\nmov.b32 {l, h}, %2;\ncvt.f32.f16 %0, l;\ncvt.f32.f16 %1, h;\n}" : "=f"(lo), "=f"(hi) : "r"(a)); }
__device__ __forceinline__ uint32_t exp2_mufu(uint32_t s) { uint32_t r; asm("ex2.approx.f16x2 %0, %1;" : "=r"(r) : "r"(s)); return r; }
__device__ __forceinline__ uint32_t exp2_fma(uint32_t s) {
  uint32_t t, u;
  asm("fma.rn.relu.f16x2 %0, %1, %2, %3;" : "=r"(t) : "r"(s), "r"(0x02000200u), "r"(0x000a000au));
  asm("mul.rn.f16x2 %0, %1, %2;" : "=r"(u) : "r"(s), "r"(0x02000200u));
  const uint32_t f = hfma2(u, 0xF800F800u, s);
  const uint32_t y = hfma2(hfma2(f, 0x45614561u, 0x27f627f6u), f, 0x05aa05aau);
  return y + (t << 10);
}
template <int J> __device__ __forceinline__ void sm_unit(const uint32_t (&s)[16], uint32_t (&p)[4]) {
  p[0] = exp2_mufu(s[4 * J]); p[1] = exp2_fma(s[4 * J + 1]); p[2] = exp2_mufu(s[4 * J + 2]); p[3] = exp2_fma(s[4 * J + 3]);
}

#define KD(lo) mk64((lo), dhi(256, 3))
#define VO(x) ((uint32_t)(x) - ((uint32_t)(x) << 16))

__device__ __forceinline__ void flush(uint32_t (&a)[6], uint32_t (&o)[6]) {
#pragma unroll
  for (int i = 0; i < 6; i++) asm volatile("add.rn.f16x2 %0, %0, %1;" : "+r"(a[i]) : "r"(o[i]) : "memory");
}
__device__ __forceinline__ void attn_fast(const uint32_t (&q0)[4], const uint32_t (&q1)[4], uint32_t (&a0)[6], uint32_t (&a1)[6], int lane, int pass) {
  const uint32_t kvfull = sb + B_KVFULL, kvempty = sb + B_KVEMPTY;
  const uint32_t kbase = dlo(sb + KV_OFF, 16), vbase = dlo(sb + KV_OFF, ONES_OFF - KV_OFF);
  uint32_t s0[16] = {}, s1[16] = {}, o0[6] = {}, o1[6] = {};
  pinu(s0); pinu(s1); pinu(o0); pinu(o1);
  {
    uint32_t p0[4]={0,0,0,0}; pinu(p0);
    uint32_t p1[4]={0,0,0,0}; pinu(p1);
    uint32_t p2[4]={0,0,0,0}; pinu(p2);
    uint32_t p3[4]={0,0,0,0}; pinu(p3);
    wg_fence(); mma_qk(s0, q0, KD(kbase)); wg_commit(); wg_wait<0>(); pinu(s0);
    uint32_t vprev = vbase - VO(512);
#pragma unroll 1
    for (int it = 0; it < 8; it++) {
      const uint32_t sA = (it & 1) * 2, ph = (it >> 1) & 1, phn = ((it + 1) >> 1) & 1;
      const uint32_t kcur = kbase + sA * 512, knxt = kbase + (sA ^ 2) * 512, vcur = vbase + VO(sA * 512);
      wg_fence();
      mma_qk(s1,q1,KD(kcur+0));
      mma_pv0(o1,p2,KD(vprev+VO(960)));
      mma_pv(o1,p3,KD(vprev+VO(992)));
      wg_commit();
      flush(a0, o0);
      sm_unit<0>(s0,p0);
      sm_unit<1>(s0,p1);
      wg_fence();
      mma_pv0(o0,p0,KD(vcur+VO(128)));
      mma_pv(o0,p1,KD(vcur+VO(160)));
      wg_commit();
      wg_wait<1>();
      if (lane==0 && it!=0) mbar_arrive(kvempty+8*((sA^2)+1));
      sm_unit<2>(s0,p2);
      sm_unit<3>(s0,p3);
      wg_fence();
      mma_qk(s0,q0,KD(kcur+256));
      mma_pv(o0,p2,KD(vcur+VO(192)));
      mma_pv(o0,p3,KD(vcur+VO(224)));
      wg_commit();
      wg_wait<1>(); pinu(s1);
      sm_unit<0>(s1,p0);
      sm_unit<1>(s1,p1);
      wg_fence();
      mma_pv(o1,p0,KD(vcur+VO(128)));
      mma_pv(o1,p1,KD(vcur+VO(160)));
      wg_commit();
      wg_wait<1>();
      sm_unit<2>(s1,p2);
      sm_unit<3>(s1,p3);
      wg_fence();
      mma_qk(s1,q1,KD(kcur+256));
      mma_pv(o1,p2,KD(vcur+VO(192)));
      mma_pv(o1,p3,KD(vcur+VO(224)));
      wg_commit();
      wg_wait<1>(); pinu(s0);
      sm_unit<0>(s0,p0);
      sm_unit<1>(s0,p1);
      wg_fence();
      mma_pv(o0,p0,KD(vcur+VO(384)));
      mma_pv(o0,p1,KD(vcur+VO(416)));
      wg_commit();
      wg_wait<1>();
      sm_unit<2>(s0,p2);
      sm_unit<3>(s0,p3);
      EVW(28); mbar_wait(kvfull+8*(sA+1), ph); EVW(29);
      wg_fence();
      mma_qk(s0,q0,KD(kcur+512));
      mma_pv(o0,p2,KD(vcur+VO(448)));
      mma_pv(o0,p3,KD(vcur+VO(480)));
      wg_commit();
      wg_wait<1>(); pinu(s1);
      sm_unit<0>(s1,p0);
      sm_unit<1>(s1,p1);
      wg_fence();
      mma_pv(o1,p0,KD(vcur+VO(384)));
      mma_pv(o1,p1,KD(vcur+VO(416)));
      wg_commit();
      wg_wait<1>();
      sm_unit<2>(s1,p2);
      sm_unit<3>(s1,p3);
      wg_fence();
      mma_qk(s1,q1,KD(kcur+512));
      mma_pv(o1,p2,KD(vcur+VO(448)));
      mma_pv(o1,p3,KD(vcur+VO(480)));
      wg_commit();
      wg_wait<1>(); pinu(s0);
      sm_unit<0>(s0,p0);
      sm_unit<1>(s0,p1);
      wg_fence();
      mma_pv(o0,p0,KD(vcur+VO(640)));
      mma_pv(o0,p1,KD(vcur+VO(672)));
      wg_commit();
      wg_wait<1>();
      if (lane==0) mbar_arrive(kvempty+8*sA);
      sm_unit<2>(s0,p2);
      sm_unit<3>(s0,p3);
      wg_fence();
      mma_qk(s0,q0,KD(kcur+768));
      mma_pv(o0,p2,KD(vcur+VO(704)));
      mma_pv(o0,p3,KD(vcur+VO(736)));
      wg_commit();
      wg_wait<1>(); pinu(s1);
      sm_unit<0>(s1,p0);
      sm_unit<1>(s1,p1);
      wg_fence();
      mma_pv(o1,p0,KD(vcur+VO(640)));
      mma_pv(o1,p1,KD(vcur+VO(672)));
      wg_commit();
      wg_wait<1>();
      sm_unit<2>(s1,p2);
      sm_unit<3>(s1,p3);
      wg_fence();
      mma_qk(s1,q1,KD(kcur+768));
      mma_pv(o1,p2,KD(vcur+VO(704)));
      mma_pv(o1,p3,KD(vcur+VO(736)));
      wg_commit();
      wg_wait<1>(); pinu(s0);
      sm_unit<0>(s0,p0);
      sm_unit<1>(s0,p1);
      wg_fence();
      mma_pv(o0,p0,KD(vcur+VO(896)));
      mma_pv(o0,p1,KD(vcur+VO(928)));
      wg_commit();
      wg_wait<1>();
      sm_unit<2>(s0,p2);
      sm_unit<3>(s0,p3);
      EVW(30); mbar_wait(kvfull+8*(sA^2), phn); EVW(14);
      wg_fence();
      mma_qk(s0,q0,KD(knxt));
      mma_pv(o0,p2,KD(vcur+VO(960)));
      mma_pv(o0,p3,KD(vcur+VO(992)));
      wg_commit();
      wg_wait<1>(); pinu(s1);
      sm_unit<0>(s1,p0);
      sm_unit<1>(s1,p1);
      wg_fence();
      mma_pv(o1,p0,KD(vcur+VO(896)));
      mma_pv(o1,p1,KD(vcur+VO(928)));
      wg_commit();
      wg_wait<1>();
      sm_unit<2>(s1,p2);
      sm_unit<3>(s1,p3);
      wg_wait<0>(); pinu(s0); pinu(o0); pinu(o1);
      flush(a1, o1);
      vprev = vcur;
    }
    wg_fence();
    mma_pv0(o1,p2,KD(vprev+VO(960)));
    mma_pv(o1,p3,KD(vprev+VO(992)));
    wg_commit(); flush(a0, o0); wg_wait<0>(); pinu(o1);
    if (lane == 0) mbar_arrive(kvempty + 8 * 3);
    flush(a1, o1);
  }
}

__device__ __forceinline__ void mma16816(float* d, const uint32_t (&a)[4], uint32_t b0, uint32_t b1) {
  asm("mma.sync.aligned.m16n8k16.row.col.f32.bf16.bf16.f32 {%0,%1,%2,%3}, {%4,%5,%6,%7}, {%8,%9}, {%0,%1,%2,%3};"
      : "+f"(d[0]), "+f"(d[1]), "+f"(d[2]), "+f"(d[3]) : "r"(a[0]), "r"(a[1]), "r"(a[2]), "r"(a[3]), "r"(b0), "r"(b1));
}
__device__ __forceinline__ uint32_t trans8(uint32_t a) { uint32_t r; asm("movmatrix.sync.aligned.m8n8.trans.b16 %0, %1;" : "=r"(r) : "r"(a)); return r; }
__device__ __forceinline__ void attn_online(const uint32_t (&qn)[4], float g0, float g1, uint8_t* dst, int pass, int lane) {
  uint32_t q[4];
#pragma unroll
  for (int i = 0; i < 4; i++) {
    const int src = (lane & ~3) | ((2 * lane + (i >> 1)) & 3);
    const uint32_t u = __shfl_sync(~0u, qn[i & 1], src), v = __shfl_sync(~0u, qn[2 + (i & 1)], src);
    q[i] = (lane & 2) ? v : u;
  }
  float o[12] = {};
  float m0 = -3e38f, m1 = -3e38f;
#pragma unroll 2
  for (int b = 0; b < 128; b++) {
    const uint4 k = __ldcg(g_kvb + b * 64 + lane), v = __ldcg(g_kvb + b * 64 + 32 + lane);
    float s[8] = {};
    mma16816(s, q, k.x, k.z); mma16816(s + 4, q, k.y, k.w);
    float x = fmaxf(fmaxf(m0, fmaxf(s[0], s[1])), fmaxf(s[4], s[5])), y = fmaxf(fmaxf(m1, fmaxf(s[2], s[3])), fmaxf(s[6], s[7]));
    x = fmaxf(x, __shfl_xor_sync(~0u, x, 1)); x = fmaxf(x, __shfl_xor_sync(~0u, x, 2));
    y = fmaxf(y, __shfl_xor_sync(~0u, y, 1)); y = fmaxf(y, __shfl_xor_sync(~0u, y, 2));
    const float cx = ex2((m0 - x) * QS), cy = ex2((m1 - y) * QS);
    m0 = x; m1 = y;
#pragma unroll
    for (int j = 0; j < 3; j++) { o[4 * j] *= cx; o[4 * j + 1] *= cx; o[4 * j + 2] *= cy; o[4 * j + 3] *= cy; }
    const uint32_t p[4] = {pack2(ex2((s[0] - x) * QS), ex2((s[1] - x) * QS)), pack2(ex2((s[2] - y) * QS), ex2((s[3] - y) * QS)),
                           pack2(ex2((s[4] - x) * QS), ex2((s[5] - x) * QS)), pack2(ex2((s[6] - y) * QS), ex2((s[7] - y) * QS))};
    mma16816(o, p, trans8(v.x), trans8(v.y)); mma16816(o + 4, p, trans8(v.z), trans8(v.w)); mma16816(o + 8, p, 0x3F803F80u, 0x3F803F80u);
  }
  const float a = __fdividef(g0, o[8]), b = __fdividef(g1, o[10]);
  const uint32_t w0 = pack2(o[0] * a, o[1] * a), w1 = pack2(o[2] * b, o[3] * b), w2 = pack2(o[4] * a, o[5] * a), w3 = pack2(o[6] * b, o[7] * b);
  if (pass == 0) {
    dst += (lane & 2) * 508 + (lane & 1) * 4;
    stg64(dst, w0, w2); stg64(dst + 128, w1, w3);
  } else {
    dst += (lane & 1) * 16 - (lane & 2) * 12;
    st_rlx64(dst, ~w0, ~w1); st_rlx64(dst + 16, ~w2, ~w3);
  }
}

__device__ __forceinline__ void store_o(const float (&o)[12], float g0, float g1, uint8_t* dst, int pass) {
  const float a = __fdividef(g0, o[8]), b = __fdividef(g1, o[10]);
  const uint32_t w0 = pack2(o[0] * a, o[1] * a), w1 = pack2(o[2] * b, o[3] * b), w2 = pack2(o[4] * a, o[5] * a), w3 = pack2(o[6] * b, o[7] * b);
  if (pass == 0) { stg32(dst, w0); stg32(dst + 128, w1); stg32(dst + 1024, w2); stg32(dst + 1152, w3); }
  else st_rlx128(dst, ~w0, ~w1, ~w2, ~w3);
}

__device__ __forceinline__ void attn_passes(uint32_t (&qh)[4][4], uint32_t (&qb)[4][4], float qn, uint8_t* odst, int wg, uint32_t (&r)[8][4], const uint8_t* src) {
  const int lane = threadIdx.x & 31;
  float g0 = 0.f, g1 = 0.f;
#pragma unroll 1
  for (int p = 0; p < 2; p++) {
    {
      uint32_t a0[6] = {}, a1[6] = {};
      attn_fast(qh[0], qh[1], a0, a1, lane, p);
      {
        uint32_t go;
        asm volatile("{\n.reg .pred p;\nmbarrier.test_wait.parity.shared::cta.b64 p, [%1], 0;\nselp.u32 %0, 1, 0, p;\n}" : "=r"(go) : "r"(sb + B_TAIL) : "memory");
#pragma unroll
        for (int j = 0; j < 8; j++) ld_rlx128(r[j], src + j * 512, PRE && go);
      }
      if (p == 0) {
        mbar_wait(sb + B_GREADY, 0);
        const uint32_t ga = sb + G_OFF + ((threadIdx.x >> 5) * 16 + (lane >> 2)) * 8;
        g0 = __uint_as_float(lds32(ga)); g1 = __uint_as_float(lds32(ga + 64));
        const float kn = __uint_as_float(lds32(sb + MISC_OFF + 32));
        qn = !FORCE_SLOW && qn * kn <= 372.f && qn <= 65536.f && kn <= 65536.f ? 128.f : NAN;
      }
      float o0[12], o1[12], hi = 0.f;
#pragma unroll
      for (int i = 0; i < 6; i++) { unpackh(a0[i], o0[2 * i], o0[2 * i + 1]); unpackh(a1[i], o1[2 * i], o1[2 * i + 1]); }
      const float lo = fminf(fminf(o0[8], o0[10]), fminf(o1[8], o1[10]));
#pragma unroll
      for (int i = 0; i < 11; i++) hi += fabsf(o0[i]) + fabsf(o1[i]);
      const bool ok = lo >= qn && hi < INFINITY;
      if (__all_sync(~0u, ok)) {
        store_o(o0, g0, g1, odst, p);
        store_o(o1, g0, g1, odst + 2048, p);
      } else {
#pragma unroll 1
        for (int h = 0; h < 2; h++) {
          attn_online(qb[0], g0, g1, odst + h * 2048, p, lane);
#pragma unroll
          for (int i = 0; i < 4; i++) qb[0][i] = qb[1][i];
        }
      }
    }
    if (p == 0) {
      odst += 32768 + (threadIdx.x & 96) * 8 + lane * 12;
      st_rlx128(odst, 0, 0, 0, 0); st_rlx128(odst + 2048, 0, 0, 0, 0);
      __syncwarp();
      if (lane == 0) mbar_arrive(sb + B_PUB + 32);
    }
#pragma unroll
    for (int i = 0; i < 4; i++) { qh[0][i] = qh[2][i]; qh[1][i] = qh[3][i]; qb[0][i] = qb[2][i]; qb[1][i] = qb[3][i]; }
  }
}

__device__ __forceinline__ uint32_t o_off(int c) { return sb + (c >> 1) * FST + (c & 1) * 4096; }
__device__ __forceinline__ void o_push(int c, int lane) {
  asm volatile("fence.proxy.async.shared::cta;" ::: "memory");
  __syncwarp();
  if (lane == 0) {
    uint32_t old;
    asm volatile("atom.shared.or.b32 %0, [%1], %2;" : "=r"(old) : "r"(sb + MISC_OFF + 40), "r"(1u << c) : "memory");
    if (!(old >> c & 1)) {
      const int pos = __popc(old);
      sts32(sb + MISC_OFF + 4 * pos, dlo(o_off(c), 1024));
      mbar_arrive(sb + B_Q + 8 * pos);
    }
  }
}

__device__ __forceinline__ float geglu(float x, float u) {
  const float y = x * fmaf(x * x, 0.044715f * 0.7978845608028654f, 0.7978845608028654f);
  float t; asm("tanh.approx.f32 %0, %1;" : "=f"(t) : "f"(y));
  const float h = x * u;
  return fmaf(h, t, h);
}
template <int N> __device__ __forceinline__ void store_h(const float (&d)[N], uint8_t* dst) {
#pragma unroll
  for (int j = 0; j < N / 8; j++) {
    stg32(dst + j * 1024, pack2(geglu(d[4 * j], d[N / 2 + 4 * j]), geglu(d[4 * j + 1], d[N / 2 + 1 + 4 * j])));
    stg32(dst + j * 1024 + 128, pack2(geglu(d[4 * j + 2], d[N / 2 + 2 + 4 * j]), geglu(d[4 * j + 3], d[N / 2 + 3 + 4 * j])));
  }
}

__device__ __forceinline__ int h_slot(int c, int u) {
  const int late = 27 - ((u >> 3) % 3);
  return c == 27 ? late : c == late ? 27 : c;
}
__device__ __forceinline__ void helper_cta(const Maps& mp, int warp, int lane) {
  const int v0 = (blockIdx.x - 128) * 24, isw = 32 - (v0 & 31);
  constexpr uint32_t HW = sb + B_XFULL, HF = sb + B_FFULL, HE = sb + B_FEMPTY, HP = sb + G_OFF;
  if (warp == 1 && lane < 3) asm volatile("prefetch.tensormap [%0];" ::"l"(lane == 0 ? &mp.x : lane == 1 ? &mp.wg : &mp.wu) : "memory");
  if (threadIdx.x < 24) {
    const int i = threadIdx.x;
    if (i < 8) { mbar_init(HW + 8 * i, 1); mbar_init(HF + 8 * i, 1); mbar_init(HE + 8 * i, 4); }
    mbar_init(HP + 8 * i, 4);
    asm volatile("fence.mbarrier_init.release.cluster;" ::: "memory");
  }
  __syncthreads();
  if (warp == 12) {
#pragma unroll 1
    for (int m = 0, s = 0, ph = 1; m < 99; m++) {
      mbar_wait(HE + 8 * s, ph);
      const int i = (m >> 2) - (~m & 1), j = ((m >> 1) & 1) + 2 * (~m & 1);
      if ((unsigned)i < 24) u_tma3d(HF + 8 * s, 16384, sb + W_OFF + s * 16384, &mp.x, 0, ((v0 + i) & 31) * 64, 2 * j);
      else if (lane < 5) mbar_arrive((lane < 4 ? HE : HF) + 8 * s);
      __syncwarp();
      const int e = m < 6 ? m + (m == 5) : m - 4 * isw - 2;
      if (e == 1 || e == 3 || e == 4 || e == 6) {
        const int hc = 25 + (v0 >> 5) + (m >= 6);
        for (int k = e & 6; k < (e & 6) + 2; k++) u_tma2d_pair(HW + 8 * k, sb + k * 16384, &mp.wg, &mp.wu, hc * 64, k * 64, k * 64);
      }
      if (++s == 6) { s = 0; ph ^= 1; }
    }
  } else if (warp == 13) {
#pragma unroll 1
    for (int i = 0; i < 24; i++) {
      mbar_wait_ns<HNP>(HP + 8 * i, 0);
      fence_gpu();
      if (lane == 0) { st_rlx(g_flags + 64 + ((v0 + i) & 31) * 64 + 2 * h_slot(25 + ((v0 + i) >> 5), (v0 + i) & 31), 1); EV(i); }
    }
  } else if (warp < 12) {
    constexpr uint32_t H128 = dhi(1024, 1);
    const uint32_t xl = dlo(sb + W_OFF, 16), wl = dlo(sb, 8192);
    const int w = warp >> 2;
    float d[64];
    zero(d);
#pragma unroll 1
    for (int i = w; i < 24; i += 3) {
      const int u = (v0 + i) & 31, hc = h_slot(25 + ((v0 + i) >> 5), u);
      if (i) asm volatile("bar.sync %0, 256;" ::"r"(1 + w) : "memory");
      int sp = 0;
#pragma unroll 1
      for (int j = 0; j < 4; j++) {
        const int m = 4 * i + 2 * j + (j < 2), s = m % 6;
        if (i < 3 || (unsigned)(i - isw) < 3) { mbar_wait(HW + 16 * j, i >= isw); mbar_wait(HW + 16 * j + 8, i >= isw); }
        mbar_wait(HF + 8 * s, (m / 6) & 1);
        wg_fence();
#pragma unroll
        for (int k = 0; k < 8; k++) mma_ss_t128(d, mk64(xl + s * 1024 + (k >> 2) * 512 + 2 * (k & 3), H128), mk64(wl + (2 * j + (k >> 2)) * 1024 + 128 * (k & 3), H128), (j | k) != 0);
        wg_commit();
        wg_wait<1>();
        if (j == 1 && i != 23) asm volatile("bar.arrive %0, 256;" ::"r"(w == 2 ? 1 : 2 + w) : "memory");
        if (j && lane == 0) mbar_arrive(HE + 8 * sp);
        sp = s;
      }
      wg_wait<0>();
      if (lane == 0) mbar_arrive(HE + 8 * sp);
      mbar_wait(HF + 56, 1);
      pin(d);
      store_h(d, g_a + (size_t)u * A_BYTES + hc * 8192 + (warp & 3) * 256 + lane * 4);
      __syncwarp();
      if (lane == 0) mbar_arrive(HP + 8 * i);
      pin(d);
    }
  }
}

__global__ void __launch_bounds__(512, 1)
fused_kernel(const __grid_constant__ Maps mp, const uint16_t* __restrict__ gate_w, const uint4* __restrict__ wk, const uint4* __restrict__ wv,
             const uint8_t* __restrict__ wd_raw, const uint8_t* __restrict__ wo_raw, uint4* __restrict__ out) {
  extern __shared__ __align__(1024) uint8_t smem[];
  const int tid = threadIdx.x, lane = tid & 31;
  const int warp = __shfl_sync(~0u, tid >> 5, 0);
  const int wg = warp >> 2, wq4 = warp & 3;
  const int tb = blockIdx.x >> 3, cg = blockIdx.x & 7;
  const int half = cg & 1;
  if (blockIdx.x >= 128) { helper_cta(mp, warp, lane); return; }
  const bool skip3 = cg < 4;

  if (warp == 12) {
    if (lane == 0) {
      EV(0);
      if ((uint32_t)__cvta_generic_to_shared(smem) != sb) __trap();
      for (int i = 0; i < 8; i++) mbar_init(sb + B_XFULL + 8 * i, 1);
      for (int i = 0; i < 4; i++) mbar_init(sb + B_WQ + 8 * i, 1);
      asm volatile("fence.mbarrier_init.release.cluster;" ::: "memory");
    }
    __syncwarp();
    const uint32_t xb = sb + B_XFULL + 32 * half, xd = sb + X_OFF + half * 65536;
    const int row = tb * 128 + half * 64;
    if (cg < 4) {
#pragma unroll
      for (int j = 0; j < 4; j++) u_tma3d(xb + 8 * j, 16384, xd + j * 16384, &mp.x, 0, row, 2 * j);
    }
#pragma unroll
    for (int j = 0; j < 4; j++) {
      u_tma2d(sb + B_WQ + 8 * j, 16384, sb + W_OFF + j * 16384, &mp.wq, cg * 64, j * 128);
      u_tma3d((xb ^ 32) + 8 * j, 16384, (xd ^ 65536) + j * 16384, &mp.x, 0, row ^ 64, 2 * j);
      if (cg >= 4) u_tma3d(xb + 8 * j, 16384, xd + j * 16384, &mp.x, 0, row, 2 * j);
    }
  } else if (tid == 416) {
    mbar_init(sb + B_GREADY, 1); mbar_init(sb + B_FFN1, 4);
    for (int i = 0; i < 4; i++) { mbar_init(sb + B_WFULL + 8 * i, 1); mbar_init(sb + B_WEMPTY + 8 * i, 8); mbar_init(sb + B_KVFULL + 8 * i, 1); mbar_init(sb + B_KVEMPTY + 8 * i, 8); mbar_init(sb + B_PUB + 8 * i, 4); }
    mbar_init(sb + B_PUB + 32, 8);
    for (int i = 0; i < 8; i++) { mbar_init(sb + B_FFULL + 8 * i, 2); mbar_init(sb + B_FEMPTY + 8 * i, 4); mbar_init(sb + B_Q + 8 * i, 1); }
    mbar_init(sb + B_TAIL, 4); sts32(sb + MISC_OFF + 40, 0);
    asm volatile("fence.mbarrier_init.release.cluster;" ::: "memory");
  } else if (tid == 448) {
    asm volatile("prefetch.tensormap [%0];" ::"l"(&mp.wg) : "memory");
    asm volatile("prefetch.tensormap [%0];" ::"l"(&mp.wu) : "memory");
    asm volatile("prefetch.tensormap [%0];" ::"l"(&mp.wd) : "memory");
    asm volatile("prefetch.tensormap [%0];" ::"l"(&mp.wo) : "memory");
    asm volatile("prefetch.tensormap [%0];" ::"l"(&mp.wg2) : "memory");
    asm volatile("prefetch.tensormap [%0];" ::"l"(&mp.wu2) : "memory");
  }
  uint4 wa[4], wb[4];
  uint32_t wz[4];
  if (cg < 4 && wg == 2) {
    const uint4* w = (cg < 2 ? wk : wv) + (tid & 127) * 2;
#pragma unroll
    for (int i = 0; i < 4; i++) { wa[i] = __ldg(w + i * 256); wb[i] = __ldg(w + i * 256 + 1); wz[i] = __ldg(gate_w + (tid & 127) + i * 128); }
  }
  if (tid < 128) { sts32(sb + ONES_OFF + tid * 4, 0x3C003C00u); asm volatile("fence.proxy.async.shared::cta;" ::: "memory"); }
  __syncthreads();
  if (tid == 0) EV(1);

  uint8_t* const a_tb = g_a + (size_t)(tb * 2) * A_BYTES;
  uint32_t* const fl_tb = g_flags + 64 + tb * 128;

  if (wg == 3) {
    asm volatile("setmaxnreg.dec.sync.aligned.u32 %0;" ::"n"(REG_PROD));
    if (wq4 == 1 || wq4 == 2) {
      if (cg < 4) asm volatile("bar.sync 4, 224;" ::: "memory");
      else mbar_wait_sleep<NS_W>(sb + B_XFULL + 16, 0);
    }
    if (wq4 == 0) {
#pragma unroll 1
      for (int n = 0; n < (skip3 ? 24 : 28); n++) {
        const int s = n & 3;
        const int c0 = n < 24 ? ((n & 24) + cg) * 64 : 24 * 64 + (cg & 2) * 16, c1 = n < 24 ? (n & 7) * 64 : s * 128;
        mbar_wait_sleep<NS_W>(sb + B_WEMPTY + 8 * s, (n >> 2) & 1);
        u_tma2d_pair(sb + B_WFULL + 8 * s, sb + W_OFF + s * 16384, n < 24 ? &mp.wg : &mp.wg2, n < 24 ? &mp.wu : &mp.wu2, c0, c1, c1);
        if (n == 8) { u_prefetch(wd_raw + blockIdx.x * 14336, 14336); u_prefetch(wo_raw + blockIdx.x * 4096, 4096); }
      }
      mbar_wait_sleep<NS_W>(sb + B_FFN1, 0);
#pragma unroll 1
      for (int n = 0; n < 36; n++) {
        const int s = n & 7;
        mbar_wait_sleep<NS_W>(sb + B_FEMPTY + 8 * s, ((n >> 3) & 1) ^ 1);
        u_tma4d(sb + B_FFULL + 8 * s, 16384, sb + s * FST + 8192, n < 28 ? &mp.wd : &mp.wo, n & 32, n < 28 ? 2 * h_slot(n, 2 * tb) : 2 * (n & 3), cg & 6);
        if (n >= 32 && lane == 0) mbar_arrive(sb + B_FFULL + 8 * s);
      }
    } else if (wq4 == 1) {
      uint32_t todo = 0x55555555u ^ (5u << 2 * (tb & 14)), rdy = 0;
#pragma unroll 1
      for (int n = 2; n < 33; n++) {
        if (n == 15 ? rdy != 0x55555555u : !(rdy & todo)) {
          for (int i = 0; n == 15 ? rdy != 0x55555555u : !(rdy & todo); i++) {
            const uint64_t f = ld_acq64(g_flags + 2 * lane);
            rdy = __ballot_sync(~0u, (uint32_t)f & (uint32_t)(f >> 32) & 1);
            rdy &= (rdy >> 1) & 0x55555555u;
            if (i > 0x100000) __trap();
          }
          fence_async_gl();
        }
        const int c = __ffs(rdy & todo) - 1, s = n & 3;
        todo ^= 1u << c;
        if (!todo) todo = 0x55555555u;
        mbar_wait_sleep<NS_KV>(sb + B_KVEMPTY + 8 * s, ((n >> 2) & 1) ^ 1);
        u_bulk(sb + B_KVFULL + 8 * s, 8192, sb + KV_OFF + s * 8192, g_kv + c * 4096);
      }
    } else if (wq4 == 3) {
      if (cg < 4) {
        uint32_t* const fl = g_flags + (tb * 2 + half) * 2 + (cg >> 1);
        asm volatile("bar.sync 4, 224;" ::: "memory");
        fence_gpu();
        if (lane == 0) { st_rlx(fl, 1); EV(2); }
        asm volatile("bar.sync 5, 160;" ::: "memory");
        const uint32_t m = __reduce_max_sync(~0u, lds32(sb + MISC_OFF + 48 + (lane & 3) * 4));
        fence_gpu();
        if (lane == 0) st_rlx(fl, m | 3);
      }
#pragma unroll 1
      for (int e = 0; e < 5; e++) {
        if (e == 3 && skip3) continue;
        mbar_wait_sleep<NS_W>(sb + B_PUB + 8 * e, 0);
        fence_gpu();
        const int idx = e < 3 ? 2 * (e * 8 + cg) : e == 3 ? 48 + (cg & 2) * 4 : 2 * cg + 1;
        if (lane < 2 && (e != 3 || lane == half)) st_rlx(fl_tb + lane * 64 + idx, 1);
      }
    } else {
      {
        mbar_wait_sleep<NS_W>(sb + B_KVEMPTY + 8 * GSL, 0);
        uint64_t f;
        for (int i = 0;; i++) {
          f = ld_acq64(g_flags + 2 * lane);
          if (__all_sync(~0u, (uint32_t)f & (uint32_t)(f >> 32) & 2)) break;
          if (i > 0x100000) __trap();
          __nanosleep(NS_F);
        }
        fence_async_gl();
        const uint32_t fk = __reduce_max_sync(~0u, max((uint32_t)f, (uint32_t)(f >> 32)));
        if (lane == 0) sts32(sb + MISC_OFF + 32, fk);
        __syncwarp();
        u_bulk(sb + B_GREADY, 1024, sb + G_OFF, g_gate + tb * 128);
      }
      mbar_wait_sleep<NS_W>(sb + B_FFN1, 0);
      const uint32_t* fl = fl_tb + half * 64 + 2 * lane;
      const uint8_t* src = a_tb + half * A_BYTES;
      int ready = 0;
#pragma unroll 1
      for (int t = 0; t < 32; t++) {
        const int n = t < 27 ? t : t < 31 ? t + 1 : 27;
        if (t >= ready) {
          for (int i = 0;; i++) {
            const uint64_t f = ld_acq64(fl);
            const uint32_t rh = __ballot_sync(~0u, (uint32_t)f != 0), ro = __ballot_sync(~0u, (f >> 32) != 0);
            ready = __ffs(~(rh & ((rh >> 4) | ~(1u << 24)) & 0x7ffffffu)) - 1;
            if (ready == 27) ready += (__ffs(~ro) - 1) >> 1;
            if (ready == 31) ready += rh >> 27 & 1;
            if (t < ready) break;
            if (i > 0x100000) __trap();
            __nanosleep(NS_F);
          }
          fence_async_gl();
        }
        const int s = n & 7;
        mbar_wait_sleep<NS_W>(sb + B_FEMPTY + 8 * s, ((n >> 3) & 1) ^ 1);
        u_bulk(sb + B_FFULL + 8 * s, 8192, sb + s * FST, src + n * 8192);
      }
      if (cg < 4) {
        for (int i = 0; !__all_sync(~0u, ld_acq(g_flags + 64 + (tb ^ 1) * 128 + 2 * (lane & 7))); i++) if (i > 0x100000) __trap();
        for (int i = 0; i < 4; i++) g_kv0[tb * 512 + cg * 128 + i * 32 + lane] = make_uint4(0, 0, 0, 0);
      }
      uint32_t last = 0;
      if (lane == 0) { __threadfence(); last = atomicAdd(&g_done, 1) == 127; __threadfence(); }
      if (__shfl_sync(~0u, last, 0)) {
        for (int i = lane; i < (64 + 32 * 64) / 4; i += 32) reinterpret_cast<uint4*>(g_flags)[i] = make_uint4(0, 0, 0, 0);
        if (lane == 0) g_done = 0;
      }
    }
  } else if (wg == 2) {
    asm volatile("setmaxnreg.inc.sync.aligned.u32 %0;" ::"n"(REG_GEMM));
    constexpr uint32_t H128 = dhi(1024, 1);
    float e[11] = {};
    if (cg < 4) {
#pragma unroll
      for (int i = 0; i < 4; i++) {
        const uint32_t a = sb + KV_OFF + i * 4096 + (tid & 127) * 32 + (tid & 4) * 4;
        sts128(a, wa[i].x, wa[i].z, wb[i].x, wb[i].z); sts128(a ^ 16, wa[i].y, wa[i].w, wb[i].y, wb[i].w); sts32(a + 16384, wz[i]);
      }
      asm volatile("fence.proxy.async.shared::cta;" ::: "memory");
      float d[12];
      zero(d);
      bar_sync(3);
      const uint32_t xl = dlo(sb + X_OFF + half * 65536, 16), wl = dlo(sb + KV_OFF, 16384);
#pragma unroll 1
      for (int j = 0; j < 4; j++) {
        mbar_wait(sb + B_XFULL + 32 * half + 8 * j, 0);
        wg_fence();
#pragma unroll
        for (int k = 0; k < 8; k++) mma_ss_t24(d, mk64(xl + j * 1024 + (k >> 2) * 512 + 2 * (k & 3), H128), KD(wl + j * 256 + 32 * k), 1);
        wg_commit();
      }
      wg_wait<0>(); pin(d);
      if ((tid & 127) == 0) EV(46);
      const float sc = cg < 2 ? 0.0625f : 1.f;
      const uint32_t w0 = packh(d[0] * sc, d[1] * sc), w1 = packh(d[4] * sc, d[5] * sc), w2 = packh(d[2] * sc, d[3] * sc), w3 = packh(d[6] * sc, d[7] * sc);
      st_rlx128(g_kv0 + tb * 512 + cg * 128 + (tid & 127), ~w0, ~w1, ~w2, ~w3);
      uint8_t* dst = g_kv + (tb * 2 + half) * 4096 + (cg >> 1) * 2048 + wq4 * 512 + ((lane * 8) ^ (lane & 16));
      stg64(dst, w0, w1); stg64(dst + 256, w2, w3);
      asm volatile("bar.arrive 4, 224;" ::: "memory");
      if ((tid & 127) == 0) EV(47);
#pragma unroll
      for (int i = 0; i < 11; i++) asm volatile("mov.b32 %0, %1;" : "=f"(e[i]) : "f"(d[i]));
    }
    {
      uint32_t r[8][4] = {}, pend = 255;
      const uint32_t a = sb + KV_OFF + wq4 * 512 + ((lane * 8) ^ (lane & 16));
#pragma unroll
      for (int h = 0; h < 2; h++) {
#pragma unroll 1
        for (int i = 0; i < 0x100000; i++) {
#pragma unroll
          for (int j = 4 * h; j < 4 * h + 4; j++) if (__all_sync(~0u, min(min(r[j][0], r[j][1]), min(r[j][2], r[j][3])) != 0)) pend &= ~(1u << j);
          if (!(pend & (15 << 4 * h))) break;
#pragma unroll
          for (int j = 4 * h; j < 4 * h + 4; j++) if (pend >> j & 1) ld_rlx128(r[j], g_kv0 + (tb ^ h) * 512 + (j & 3) * 128 + (tid & 127), 1);
        }
        if (h == 0 && cg < 4) bar_sync(3);
#pragma unroll
        for (int j = 4 * h; j < 4 * h + 4; j++) {
          const uint32_t b = a + h * 8192 + (j & 1) * 4096 + (j & 2) * 1024;
          sts64(b, ~r[j][0], ~r[j][1]); sts64(b + 256, ~r[j][2], ~r[j][3]);
        }
        asm volatile("fence.proxy.async.shared::cta;" ::: "memory");
        if (h == 0) {
#pragma unroll
          for (int j = 4; j < 8; j++) ld_rlx128(r[j], g_kv0 + (tb ^ 1) * 512 + (j & 3) * 128 + (tid & 127), 1);
        }
        bar_sync(3);
        if (tid == 256) { mbar_arrive(sb + B_KVFULL + 8 * h); EV(h ? 53 : 45); }
        if (h == 1 && cg < 4) {
          g_kvb[(tb * 8 + half * 4 + wq4) * 64 + (cg >> 1) * 32 + lane] = make_uint4(pack2(e[0], e[1]), pack2(e[2], e[3]), pack2(e[4], e[5]), pack2(e[6], e[7]));
          uint32_t mx;
          if (cg < 2) {
            const float z0 = __shfl_sync(~0u, e[8], (lane & 7) * 4), z1 = __shfl_sync(~0u, e[10], (lane & 7) * 4);
            const float g = 1.f / (1.f + __expf((lane & 8) ? -z1 : -z0));
            if (lane < 16) g_gate[tb * 128 + half * 64 + wq4 * 16 + lane] = make_float2(g, 0.5f * (1.f - g));
            float n0 = sq4(e[0], e[1], e[4], e[5]), n1 = sq4(e[2], e[3], e[6], e[7]);
            n0 += __shfl_xor_sync(~0u, n0, 1); n1 += __shfl_xor_sync(~0u, n1, 1);
            n0 += __shfl_xor_sync(~0u, n0, 2); n1 += __shfl_xor_sync(~0u, n1, 2);
            mx = __reduce_max_sync(~0u, max(__float_as_uint(n0), __float_as_uint(n1)));
          } else {
            bool ok = true;
#pragma unroll
            for (int i = 0; i < 4; i++) {
              const int j = (i & 1) + (i >> 1) * 4;
              uint32_t c = max(__float_as_uint(e[j]) & 0x7fffffffu, __float_as_uint(e[j + 2]) & 0x7fffffffu);
              c = max(c, __shfl_xor_sync(~0u, c, 4)); c = max(c, __shfl_xor_sync(~0u, c, 8)); c = max(c, __shfl_xor_sync(~0u, c, 16));
              ok = ok && (c == 0 || (c >= 0x37800000u && c <= 0x47000000u));
            }
            mx = __all_sync(~0u, ok) ? 0 : 0x7f800001u;
          }
          if (lane == 0) sts32(sb + MISC_OFF + 48 + wq4 * 4, mx);
          asm volatile("bar.arrive 5, 160;" ::: "memory");
          if ((tid & 127) == 0) EV(52);
        }
      }
    }
    float d0[64], d1[64];
    zero(d0); zero(d1);
    if (QFIRST) mbar_wait(sb + B_WEMPTY + 24, 0);
    const uint32_t xl = dlo(sb + X_OFF, 16), wl = dlo(sb + W_OFF, 8192);
    uint8_t* const hdst = a_tb + wq4 * 256 + lane * 4;
    const uint32_t grow = sb + G_OFF + (wq4 * 16 + (lane >> 2)) * 8 + 4;
#pragma unroll 1
    for (int st = 0; st < 3; st++) {
#pragma unroll 1
      for (int kc = 0; kc < 8; kc++) {
        const int s = kc & 3;
        if (!QFIRST && st == 0) { mbar_wait(sb + B_XFULL + 8 * (kc >> 1), 0); mbar_wait(sb + B_XFULL + 32 + 8 * (kc >> 1), 0); }
        mbar_wait(sb + B_WFULL + 8 * s, (kc >> 2) & 1);
        const uint32_t a = xl + kc * 512, b = wl + s * 1024;
#pragma unroll
        for (int k = 0; k < 4; k++) {
          wg_fence();
          mma_ss_t128(d0, mk64(a + 2 * k, H128), mk64(b + 128 * k, H128), (kc | k) != 0);
          mma_ss_t128(d1, mk64(a + 4096 + 2 * k, H128), mk64(b + 128 * k, H128), (kc | k) != 0);
          wg_commit(); wg_wait<GW1>();
          if (GW1 && k == 0 && kc != 0 && lane == 0) mbar_arrive2(sb + B_WEMPTY + 8 * ((s + 3) & 3));
        }
        if (!GW1 && lane == 0) mbar_arrive2(sb + B_WEMPTY + 8 * s);
      }
      if (GW1) { wg_wait<0>(); if (lane == 0) mbar_arrive2(sb + B_WEMPTY + 8 * 3); }
      pin(d0); pin(d1);
      if (st == 2 && skip3 && lane == 0) mbar_arrive(sb + B_FFN1);
      if (st == 0 && tid == 256) EV(8);
      if (st == 0) mbar_wait(sb + B_GREADY, 0);
      const int hc = st * 8 + cg;
      store_h(d0, hdst + hc * 8192);
      store_h(d1, hdst + A_BYTES + hc * 8192);
      __syncwarp();
      if (lane == 0) mbar_arrive(sb + B_PUB + 8 * st);
      pin(d0); pin(d1);
    }
    if (!skip3) {
      float d2[32];
      zero(d2);
#pragma unroll 1
      for (int s = 0; s < 4; s++) {
        mbar_wait(sb + B_WFULL + 8 * s, 0);
        const uint32_t a = xl + s * 1024 + half * 4096, b = wl + s * 1024;
#pragma unroll
        for (int k = 0; k < 8; k += S3K) {
          wg_fence();
#pragma unroll
          for (int i = k; i < k + S3K; i++) mma_ss_t64(d2, mk64(a + (i >> 2) * 512 + 2 * (i & 3), H128), mk64(b + 64 * i, dhi(512, 2)), 1);
          wg_commit(); wg_wait<0>();
        }
      }
      pin(d2);
      if (lane == 0) mbar_arrive(sb + B_FFN1);
      if (tid == 256) EV(12);
      store_h(d2, hdst + half * A_BYTES + 24 * 8192 + (cg & 2) * 2048);
      __syncwarp();
      if (lane == 0) mbar_arrive(sb + B_PUB + 24);
    }
    const uint32_t al = dlo(sb, 1024), bl = dlo(sb + 8192, 8192);
    constexpr uint32_t HA = dhi(128, 0);
    auto fin = [&](int n0, int n1) {
#pragma unroll 1
      for (int n = n0; n < n1; n++) {
        const int s = n & 7;
        mbar_wait_sleep<NS_G>(sb + B_FFULL + 8 * s, (n >> 3) & 1);
        const uint32_t a = al + s * (FST >> 4), b = bl + s * (FST >> 4);
#pragma unroll
        for (int k = 0; k < 4; k += 2) {
          wg_fence();
#pragma unroll
          for (int i = k; i < k + 2; i++) mma_ss_t128(d0, mk64(a + 128 * i, HA), mk64(b + 128 * i, H128), n0 != 0 || (n | i) != 0);
          wg_commit(); wg_wait<1>();
          if (n0 == 0 && k == 0 && n != 0 && lane == 0) mbar_arrive(sb + B_FEMPTY + 8 * ((s + 7) & 7));
        }
      }
    };
    fin(0, 28);
    wg_wait<0>();
    pin(d0);
    if (lane == 0) { mbar_arrive(sb + B_FEMPTY + 24); mbar_arrive(sb + B_TAIL); }
    {
      const float c0 = __uint_as_float(lds32(grow + half * 512)), c1 = __uint_as_float(lds32(grow + half * 512 + 64));
#pragma unroll
      for (int i = 0; i < 64; i++) d0[i] *= (i & 2) ? c1 : c0;
    }
    pin(d0);
    fin(28, 32);
    if (tid == 256) EV(18);
#pragma unroll
    for (int s = 0; s < 4; s++) mbar_wait(sb + B_FFULL + 8 * s, 0);
    if (tid == 256) EV(31);
#pragma unroll 1
    for (int n = 0; n < 8; n++) {
      mbar_wait(sb + B_Q + 8 * n, 0);
      const uint32_t a = lds32(sb + MISC_OFF + 4 * n);
      wg_fence();
      mma_ss_t128(d0, mk64(a, HA), mk64(a + (bl - al), H128), 1);
      mma_ss_t128(d0, mk64(a + 128, HA), mk64(a + (bl - al) + 128, H128), 1);
      wg_commit();
    }
    wg_wait<0>();
    pin(d0);
    if (tid == 256) EV(19);
    const uint32_t stg = sb + 4 * FST + wq4 * 256;
#pragma unroll
    for (int j = 0; j < 8; j++) {
      const int c = (2 * j + (lane >> 4)) & 7;
      stsm4(stg + (j >> 2) * FST + c * 1024 + ((lane & 15) ^ c) * 16, pack2(d0[8 * j], d0[8 * j + 1]), pack2(d0[8 * j + 2], d0[8 * j + 3]), pack2(d0[8 * j + 4], d0[8 * j + 5]), pack2(d0[8 * j + 6], d0[8 * j + 7]));
    }
    __syncwarp();
    uint4* const op = out + (tb * 128 + half * 64 + wq4 * 16 + (lane >> 4)) * 64 + (cg & 6) * 8 + (lane & 15);
#pragma unroll
    for (int j = 0; j < 8; j++) {
      uint4 v;
      asm volatile("ld.shared.v4.u32 {%0, %1, %2, %3}, [%4];" : "=r"(v.x), "=r"(v.y), "=r"(v.z), "=r"(v.w) : "r"(stg + ((lane >> 3) & 1) * FST + (lane & 7) * 1024 + ((2 * j + (lane >> 4)) ^ (lane & 7)) * 16) : "memory");
      op[j * 128] = v;
    }
    if (tid == 256) EV(20);
  } else {
    asm volatile("setmaxnreg.inc.sync.aligned.u32 %0;" ::"n"(REG_ATT));
    constexpr uint32_t H128 = dhi(1024, 1);
    const uint32_t xl = dlo(sb + X_OFF + wg * 65536, 16);
    uint32_t qh[4][4], qb[4][4];
    float qn;
    {
      float d[32];
      zero(d);
      const uint32_t wl = dlo(sb + W_OFF, 8192);
#pragma unroll 1
      for (int s = 0; s < 4; s++) {
        mbar_wait(sb + B_WQ + 8 * s, 0);
        mbar_wait(sb + B_XFULL + 32 * wg + 8 * s, 0);
        wg_fence();
#pragma unroll
        for (int k = 0; k < 8; k++) mma_ss_t64(d, mk64(xl + (2 * s + (k >> 2)) * 512 + 2 * (k & 3), H128), mk64(wl + s * 1024 + 128 * k, H128), 1);
        wg_commit();
        wg_wait<0>();
        if (lane == 0) mbar_arrive(sb + B_WEMPTY + 8 * s);
      }
      pin(d);
      if (tid == 0) EV(44);
      uint32_t nm = 0;
#pragma unroll
      for (int h = 0; h < 4; h++) {
        const float* dh = d + 8 * h;
#pragma unroll
        for (int i = 0; i < 4; i++) {
          const float c = (i & 1) ? QS / 32.f : QS * 16.f;
          qh[h][i] = packh(dh[2 * i] * c, dh[2 * i + 1] * c);
          qb[h][i] = pack2(dh[2 * i], dh[2 * i + 1]);
        }
        float n0 = sq4(dh[0], dh[1], dh[4], dh[5]), n1 = sq4(dh[2], dh[3], dh[6], dh[7]);
        n0 += __shfl_xor_sync(~0u, n0, 1); n1 += __shfl_xor_sync(~0u, n1, 1);
        n0 += __shfl_xor_sync(~0u, n0, 2); n1 += __shfl_xor_sync(~0u, n1, 2);
        nm = max(nm, max(__float_as_uint(n0), __float_as_uint(n1)));
      }
      qn = __uint_as_float(nm) * (QS * QS);
    }
    if (tid == 0) EV(3);
    mbar_wait(sb + B_KVFULL, 0);
    if (tid == 0) { EV(5); EVC(0); }
    uint8_t* odst = a_tb + wg * A_BYTES + (224 + cg * 4) * 1024 + wq4 * 256 + lane * 4;
    const uint8_t* src = a_tb + half * A_BYTES + 256 * 1024 + warp * 4096 + lane * 16;
    uint32_t r[8][4];
    attn_passes(qh, qb, qn, odst, wg, r, src);
    mbar_wait(sb + B_TAIL, 0);
    const uint32_t dst = o_off(warp) + (lane >> 4) * 1024 + (lane & 15) * 16;
    uint32_t pend = 255;
#pragma unroll 1
    for (int i = 0; i < 0x100000; i++) {
#pragma unroll
      for (int j = 0; j < 8; j++) if (__all_sync(~0u, min(min(r[j][0], r[j][1]), min(r[j][2], r[j][3])) != 0)) {
        stsm4(dst + (j >> 2) * 2048 + (j & 3) * 256, ~r[j][0], ~r[j][1], ~r[j][2], ~r[j][3]);
        pend ^= 1u << j;
      }
      if (!pend) break;
#pragma unroll
      for (int j = 0; j < 8; j++) ld_rlx128(r[j], src + j * 512, pend & (1u << j));
    }
    o_push(warp, lane);
  }
}

typedef CUresult (*EncodeFn)(CUtensorMap*, CUtensorMapDataType, cuuint32_t, void*, const cuuint64_t*, const cuuint64_t*, const cuuint32_t*, const cuuint32_t*,
                             CUtensorMapInterleave, CUtensorMapSwizzle, CUtensorMapL2promotion, CUtensorMapFloatOOBfill);

void make_map(EncodeFn fn, CUtensorMap* m, const void* p, uint64_t cols, uint64_t rows, uint32_t bc, uint32_t br, CUtensorMapSwizzle sw) {
  cuuint64_t dims[2] = {cols, rows}, strides[1] = {cols * 2};
  cuuint32_t box[2] = {bc, br}, es[2] = {1, 1};
  fn(m, CU_TENSOR_MAP_DATA_TYPE_BFLOAT16, 2, const_cast<void*>(p), dims, strides, box, es, CU_TENSOR_MAP_INTERLEAVE_NONE, sw,
     CU_TENSOR_MAP_L2_PROMOTION_L2_128B, CU_TENSOR_MAP_FLOAT_OOB_FILL_NONE);
}

void make_map3(EncodeFn fn, CUtensorMap* m, const void* p, uint64_t bw, uint64_t nblk, uint64_t rows, uint32_t bc, uint32_t br, CUtensorMapSwizzle sw) {
  cuuint64_t dims[3] = {bw, rows, nblk}, strides[2] = {bw * nblk * 2, bw * 2};
  cuuint32_t box[3] = {bc, br, 2}, es[3] = {1, 1, 1};
  fn(m, CU_TENSOR_MAP_DATA_TYPE_BFLOAT16, 3, const_cast<void*>(p), dims, strides, box, es, CU_TENSOR_MAP_INTERLEAVE_NONE, sw,
     CU_TENSOR_MAP_L2_PROMOTION_L2_128B, CU_TENSOR_MAP_FLOAT_OOB_FILL_NONE);
}

void make_map4(EncodeFn fn, CUtensorMap* m, const void* p, uint64_t rows, uint64_t rg) {
  cuuint64_t dims[4] = {64, rg, rows / rg, 8}, strides[3] = {1024, rg * 1024, 128};
  cuuint32_t box[4] = {64, 32, 2, 2}, es[4] = {1, 1, 1, 1};
  fn(m, CU_TENSOR_MAP_DATA_TYPE_BFLOAT16, 4, const_cast<void*>(p), dims, strides, box, es, CU_TENSOR_MAP_INTERLEAVE_NONE, CU_TENSOR_MAP_SWIZZLE_128B,
     CU_TENSOR_MAP_L2_PROMOTION_L2_128B, CU_TENSOR_MAP_FLOAT_OOB_FILL_NONE);
}

}

extern "C" void kernel_launch(void* const* d_in, const int* in_sizes, int n_in, void* d_out, int out_size) {
  void* fp = nullptr;
  cudaDriverEntryPointQueryResult qr;
  cudaGetDriverEntryPoint("cuTensorMapEncodeTiled", &fp, cudaEnableDefault, &qr);
  EncodeFn fn = (EncodeFn)fp;
  Maps mp;
  make_map3(fn, &mp.x, d_in[0], 64, 8, S_, 64, 64, CU_TENSOR_MAP_SWIZZLE_128B);
  make_map(fn, &mp.wq, d_in[1], D_, D_, 64, 128, CU_TENSOR_MAP_SWIZZLE_128B);
  make_map4(fn, &mp.wo, d_in[4], D_, 64);
  make_map(fn, &mp.wg, d_in[6], F_, D_, 64, 64, CU_TENSOR_MAP_SWIZZLE_128B);
  make_map(fn, &mp.wu, d_in[7], F_, D_, 64, 64, CU_TENSOR_MAP_SWIZZLE_128B);
  make_map4(fn, &mp.wd, d_in[8], F_, 32);
  make_map(fn, &mp.wg2, d_in[6], F_, D_, 32, 128, CU_TENSOR_MAP_SWIZZLE_64B);
  make_map(fn, &mp.wu2, d_in[7], F_, D_, 32, 128, CU_TENSOR_MAP_SWIZZLE_64B);
  cudaFuncSetAttribute(fused_kernel, cudaFuncAttributeMaxDynamicSharedMemorySize, SMEM_BYTES);
  fused_kernel<<<132, 512, SMEM_BYTES, cudaStreamPerThread>>>(mp, (const uint16_t*)d_in[9], (const uint4*)d_in[2], (const uint4*)d_in[3], (const uint8_t*)d_in[8], (const uint8_t*)d_in[4], (uint4*)d_out);
}
```

```cpp
#include <cuda_runtime.h>
#include <cuda_bf16.h>
#include <cuda.h>
#include <stdint.h>

#define DEG 2
#define REG_ATT 160
#define REG_GEMM 160
#define REG_PROD 32
#define FORCE_SLOW 0
#define NS_W 100
#define NS_KV 200
#define NS_F 200
#define NS_G 50
#define GW1 0
#define HINT 4000
#define PRE 1
#define GSL 1
#define QFIRST 1
#define HNP 200
#define S3K 4

namespace {

constexpr int S_ = 2048, D_ = 512, F_ = 1792;
constexpr float QS = 0.25f * 1.4426950408889634f;

constexpr uint32_t sb = 1024;
constexpr uint32_t X_OFF = 0;
constexpr uint32_t W_OFF = 131072;
constexpr uint32_t KV_OFF = 196608;
constexpr uint32_t ONES_OFF = 229376;
constexpr uint32_t G_OFF = 229888;
constexpr uint32_t MISC_OFF = 231552;
constexpr uint32_t BAR_OFF = 231616;
constexpr uint32_t B_XFULL = BAR_OFF;
constexpr uint32_t B_PUB = B_XFULL + 64;
constexpr uint32_t B_GREADY = B_XFULL + 128;
constexpr uint32_t B_FFN1 = B_GREADY + 8;
constexpr uint32_t B_WFULL = B_FFN1 + 8;
constexpr uint32_t B_WEMPTY = B_WFULL + 32;
constexpr uint32_t B_KVFULL = B_WEMPTY + 32;
constexpr uint32_t B_KVEMPTY = B_KVFULL + 32;
constexpr uint32_t B_FFULL = B_KVEMPTY + 32;
constexpr uint32_t B_FEMPTY = B_FFULL + 64;
constexpr uint32_t B_WQ = B_FEMPTY + 64;
constexpr uint32_t B_TAIL = B_WQ + 32;
constexpr uint32_t B_Q = B_TAIL + 8;
constexpr uint32_t SMEM_BYTES = B_Q + 64;
constexpr uint32_t FST = 24576;
static_assert(SMEM_BYTES <= 232448, "smem");

constexpr int A_BYTES = 288 * 1024;
__device__ __align__(1024) uint8_t g_kv[32 * 4096];
__device__ uint4 g_kv0[16 * 512];
__device__ uint4 g_kvb[128 * 64];
__device__ __align__(1024) float2 g_gate[S_];
__device__ __align__(1024) uint8_t g_a[32 * A_BYTES];
__device__ __align__(256) uint32_t g_flags[64 + 32 * 64];
__device__ uint32_t g_done;

#define EV(i)
#define EVC(i)
struct Maps { CUtensorMap x, wq, wo, wg, wu, wd, wg2, wu2; };

__device__ __forceinline__ void wg_fence() { asm volatile("wgmma.fence.sync.aligned;" ::: "memory"); }
__device__ __forceinline__ void wg_commit() { asm volatile("wgmma.commit_group.sync.aligned;" ::: "memory"); }
template <int N> __device__ __forceinline__ void wg_wait() { asm volatile("wgmma.wait_group.sync.aligned %0;" ::"n"(N) : "memory"); }
template <int N> __device__ __forceinline__ void pin(float (&d)[N]) {
#pragma unroll
  for (int i = 0; i < N; i++) asm volatile("" : "+f"(d[i])::"memory");
}
template <int N> __device__ __forceinline__ void pinu(uint32_t (&d)[N]) {
#pragma unroll
  for (int i = 0; i < N; i++) asm volatile("" : "+r"(d[i])::"memory");
}
template <int N> __device__ __forceinline__ void zero(float (&d)[N]) {
#pragma unroll
  for (int i = 0; i < N; i++) d[i] = 0.f;
  pin(d);
}
__device__ __forceinline__ uint64_t mk64(uint32_t lo, uint32_t hi) { return ((uint64_t)hi << 32) | lo; }
__host__ __device__ constexpr uint32_t dhi(uint32_t sbo, uint32_t sw) { return (sbo >> 4) | (sw << 30); }
__device__ __forceinline__ uint32_t dlo(uint32_t addr, uint32_t lbo) { return (addr >> 4) | ((lbo >> 4) << 16); }

__device__ __forceinline__ void mbar_init(uint32_t b, uint32_t n) { asm volatile("mbarrier.init.shared::cta.b64 [%0], %1;" ::"r"(b), "r"(n) : "memory"); }
__device__ __forceinline__ void mbar_arrive(uint32_t b) { asm volatile("mbarrier.arrive.shared::cta.b64 _, [%0];" ::"r"(b) : "memory"); }
__device__ __forceinline__ void mbar_arrive2(uint32_t b) { asm volatile("mbarrier.arrive.shared::cta.b64 _, [%0], 2;" ::"r"(b) : "memory"); }
__device__ __forceinline__ void mbar_expect(uint32_t b, uint32_t bytes) { asm volatile("mbarrier.arrive.expect_tx.shared::cta.b64 _, [%0], %1;" ::"r"(b), "r"(bytes) : "memory"); }
__device__ __forceinline__ void mbar_wait(uint32_t b, uint32_t parity) {
  asm volatile(
      "{\n.reg .pred p;\n.reg .u32 c;\n"
      "mbarrier.try_wait.parity.shared::cta.b64 p, [%0], %1;\n"
      "@p bra DONE;\n"
      "mov.u32 c, 0;\n"
      "SPIN:\n"
      "mbarrier.try_wait.parity.shared::cta.b64 p, [%0], %1;\n"
      "@p bra DONE;\n"
      "add.u32 c, c, 1;\n"
      "setp.lt.u32 p, c, 0x100000;\n"
      "@p bra SPIN;\n"
      "trap;\n"
      "DONE:\n}\n" ::"r"(b), "r"(parity) : "memory");
}
template <int NS> __device__ __forceinline__ void mbar_wait_sleep(uint32_t b, uint32_t parity) {
  asm volatile(
      "{\n.reg .pred p;\n.reg .u32 c;\n"
      "mov.u32 c, 0;\n"
      "SPIN:\n"
      "mbarrier.try_wait.parity.shared::cta.b64 p, [%0], %1, %2;\n"
      "@p bra.uni DONE;\n"
      "add.u32 c, c, 1;\n"
      "setp.lt.u32 p, c, 0x40000;\n"
      "@p bra.uni SPIN;\n"
      "trap;\n"
      "DONE:\n}\n" ::"r"(b), "r"(parity), "n"(HINT) : "memory");
}
template <int NS> __device__ __forceinline__ void mbar_wait_ns(uint32_t b, uint32_t parity) {
  asm volatile(
      "{\n.reg .pred p;\n.reg .u32 c;\n"
      "mov.u32 c, 0;\n"
      "SPIN:\n"
      "mbarrier.test_wait.parity.shared::cta.b64 p, [%0], %1;\n"
      "@p bra.uni DONE;\n"
      "nanosleep.u32 %2;\n"
      "add.u32 c, c, 1;\n"
      "setp.lt.u32 p, c, 0x100000;\n"
      "@p bra.uni SPIN;\n"
      "trap;\n"
      "DONE:\n}\n" ::"r"(b), "r"(parity), "n"(NS) : "memory");
}
#define ELECT "{\n.reg .pred p;\nelect.sync _|p, 0xffffffff;\n@p mbarrier.arrive.expect_tx.shared::cta.b64 _, [%0], %1;\n"
__device__ __forceinline__ void u_tma3d(uint32_t bar, uint32_t bytes, uint32_t dst, const CUtensorMap* m, int c0, int c1, int c2) {
  asm volatile(ELECT "@p cp.async.bulk.tensor.3d.shared::cluster.global.mbarrier::complete_tx::bytes [%2], [%3, {%4, %5, %6}], [%0];\n}\n" ::"r"(bar), "r"(bytes), "r"(dst), "l"(m), "r"(c0), "r"(c1), "r"(c2) : "memory");
}
__device__ __forceinline__ void u_tma4d(uint32_t bar, uint32_t bytes, uint32_t dst, const CUtensorMap* m, int c1, int c2, int c3) {
  asm volatile(ELECT "@p cp.async.bulk.tensor.4d.shared::cluster.global.mbarrier::complete_tx::bytes [%2], [%3, {0, %4, %5, %6}], [%0];\n}\n" ::"r"(bar), "r"(bytes), "r"(dst), "l"(m), "r"(c1), "r"(c2), "r"(c3) : "memory");
}
__device__ __forceinline__ void u_tma2d(uint32_t bar, uint32_t bytes, uint32_t dst, const CUtensorMap* m, int c0, int c1) {
  asm volatile(ELECT "@p cp.async.bulk.tensor.2d.shared::cluster.global.mbarrier::complete_tx::bytes [%2], [%3, {%4, %5}], [%0];\n}\n" ::"r"(bar), "r"(bytes), "r"(dst), "l"(m), "r"(c0), "r"(c1) : "memory");
}
__device__ __forceinline__ void u_tma2d_pair(uint32_t bar, uint32_t dst, const CUtensorMap* m0, const CUtensorMap* m1, int c0, int c1, int c1b) {
  asm volatile(ELECT "@p cp.async.bulk.tensor.2d.shared::cluster.global.mbarrier::complete_tx::bytes [%2], [%3, {%5, %6}], [%0];\n"
               "@p cp.async.bulk.tensor.2d.shared::cluster.global.mbarrier::complete_tx::bytes [%2 + 8192], [%4, {%5, %7}], [%0];\n}\n" ::"r"(bar), "r"(16384), "r"(dst), "l"(m0), "l"(m1), "r"(c0), "r"(c1), "r"(c1b) : "memory");
}
__device__ __forceinline__ void u_bulk(uint32_t bar, uint32_t bytes, uint32_t dst, const void* src) {
  asm volatile(ELECT "@p cp.async.bulk.shared::cluster.global.mbarrier::complete_tx::bytes [%2], [%3], %1, [%0];\n}\n" ::"r"(bar), "r"(bytes), "r"(dst), "l"(src) : "memory");
}
__device__ __forceinline__ void u_prefetch(const void* src, uint32_t bytes) {
  asm volatile("{\n.reg .pred p;\nelect.sync _|p, 0xffffffff;\n@p cp.async.bulk.prefetch.L2.global [%0], %1;\n}\n" ::"l"(src), "r"(bytes) : "memory");
}
__device__ __forceinline__ void fence_gpu() { asm volatile("fence.acq_rel.gpu;" ::: "memory"); }
__device__ __forceinline__ void st_rlx(uint32_t* p, uint32_t v) { asm volatile("st.relaxed.gpu.global.u32 [%0], %1;" ::"l"(p), "r"(v) : "memory"); }
__device__ __forceinline__ void st_rlx64(void* p, uint32_t a, uint32_t b) { asm volatile("st.relaxed.gpu.global.v2.u32 [%0], {%1, %2};" ::"l"(p), "r"(a), "r"(b) : "memory"); }
__device__ __forceinline__ void st_rlx128(void* p, uint32_t a, uint32_t b, uint32_t c, uint32_t d) { asm volatile("st.relaxed.gpu.global.v4.u32 [%0], {%1, %2, %3, %4};" ::"l"(p), "r"(a), "r"(b), "r"(c), "r"(d) : "memory"); }
__device__ __forceinline__ void ld_rlx128(uint32_t (&v)[4], const void* p, uint32_t c) {
  asm volatile("{\n.reg .pred p;\nsetp.ne.u32 p, %5, 0;\nmov.u32 %0, 0;\nmov.u32 %1, 0;\nmov.u32 %2, 0;\nmov.u32 %3, 0;\n@p ld.relaxed.gpu.global.v4.u32 {%0, %1, %2, %3}, [%4];\n}" : "=r"(v[0]), "=r"(v[1]), "=r"(v[2]), "=r"(v[3]) : "l"(p), "r"(c) : "memory");
}
__device__ __forceinline__ uint64_t ld_acq64(const uint32_t* p) { uint64_t v; asm volatile("ld.acquire.gpu.global.u64 %0, [%1];" : "=l"(v) : "l"(p) : "memory"); return v; }
__device__ __forceinline__ void tma2d(uint32_t dst, const CUtensorMap* m, int c0, int c1, uint32_t bar) {
  asm volatile("cp.async.bulk.tensor.2d.shared::cluster.global.mbarrier::complete_tx::bytes [%0], [%1, {%3, %4}], [%2];" ::"r"(dst), "l"(m), "r"(bar), "r"(c0), "r"(c1) : "memory");
}
__device__ __forceinline__ void bulk_ld(uint32_t dst, const void* src, uint32_t bytes, uint32_t bar) {
  asm volatile("cp.async.bulk.shared::cluster.global.mbarrier::complete_tx::bytes [%0], [%1], %2, [%3];" ::"r"(dst), "l"(src), "r"(bytes), "r"(bar) : "memory");
}
__device__ __forceinline__ void l2_prefetch(const void* src, uint32_t bytes) {
  asm volatile("cp.async.bulk.prefetch.L2.global [%0], %1;" ::"l"(src), "r"(bytes) : "memory");
}
__device__ __forceinline__ uint32_t ld_acq(const uint32_t* p) { uint32_t v; asm volatile("ld.acquire.gpu.global.u32 %0, [%1];" : "=r"(v) : "l"(p) : "memory"); return v; }
__device__ __forceinline__ void st_rel(uint32_t* p, uint32_t v) { asm volatile("st.release.gpu.global.u32 [%0], %1;" ::"l"(p), "r"(v) : "memory"); }
__device__ __forceinline__ void fence_async_all() { asm volatile("fence.proxy.async;" ::: "memory"); }
__device__ __forceinline__ void fence_async_gl() { asm volatile("fence.proxy.async.global;" ::: "memory"); }
__device__ __forceinline__ void bar_sync(int id) { asm volatile("bar.sync %0, 128;" ::"r"(id) : "memory"); }
__device__ __forceinline__ uint32_t pack2(float lo, float hi) { uint32_t r; asm("cvt.rn.bf16x2.f32 %0, %1, %2;" : "=r"(r) : "f"(hi), "f"(lo)); return r; }
__device__ __forceinline__ float ex2(float a) { float r; asm("ex2.approx.ftz.f32 %0, %1;" : "=f"(r) : "f"(a)); return r; }
__device__ __forceinline__ float sq4(float a, float b, float c, float d) { return fmaf(a, a, b * b) + fmaf(c, c, d * d); }
__device__ __forceinline__ void stg32(void* p, uint32_t v) { asm volatile("st.global.u32 [%0], %1;" ::"l"(p), "r"(v) : "memory"); }
__device__ __forceinline__ void stg64(void* p, uint32_t a, uint32_t b) { asm volatile("st.global.v2.u32 [%0], {%1, %2};" ::"l"(p), "r"(a), "r"(b) : "memory"); }
__device__ __forceinline__ void sts128(uint32_t a, uint32_t x, uint32_t y, uint32_t z, uint32_t w) { asm volatile("st.shared.v4.u32 [%0], {%1, %2, %3, %4};" ::"r"(a), "r"(x), "r"(y), "r"(z), "r"(w) : "memory"); }
__device__ __forceinline__ void stsm4(uint32_t a, uint32_t x, uint32_t y, uint32_t z, uint32_t w) { asm volatile("stmatrix.sync.aligned.m8n8.x4.shared.b16 [%0], {%1,%2,%3,%4};" ::"r"(a), "r"(x), "r"(y), "r"(z), "r"(w) : "memory"); }
__device__ __forceinline__ void sts64(uint32_t a, uint32_t x, uint32_t y) { asm volatile("st.shared.v2.u32 [%0], {%1, %2};" ::"r"(a), "r"(x), "r"(y) : "memory"); }
__device__ __forceinline__ void sts32(uint32_t a, uint32_t v) { asm volatile("st.shared.u32 [%0], %1;" ::"r"(a), "r"(v) : "memory"); }
__device__ __forceinline__ uint32_t lds32(uint32_t a) { uint32_t v; asm volatile("ld.shared.u32 %0, [%1];" : "=r"(v) : "r"(a) : "memory"); return v; }

__device__ __forceinline__ void mma_qk(uint32_t (&d)[16], const uint32_t (&a)[4], uint64_t b) {
  asm volatile("{\n.reg .pred p;\nsetp.ne.b32 p, 0, 0;\n"
    "wgmma.mma_async.sync.aligned.m64n64k16.f16.f16.f16 {%0,%1,%2,%3,%4,%5,%6,%7,%8,%9,%10,%11,%12,%13,%14,%15}, {%16,%17,%18,%19}, %20, p, 1, 1, 0;\n}\n"
    : "+r"(d[0]),"+r"(d[1]),"+r"(d[2]),"+r"(d[3]),"+r"(d[4]),"+r"(d[5]),"+r"(d[6]),"+r"(d[7]),"+r"(d[8]),"+r"(d[9]),"+r"(d[10]),"+r"(d[11]),"+r"(d[12]),"+r"(d[13]),"+r"(d[14]),"+r"(d[15]) : "r"(a[0]),"r"(a[1]),"r"(a[2]),"r"(a[3]),"l"(b));
}
__device__ __forceinline__ void mma_pv(uint32_t (&d)[6], const uint32_t (&a)[4], uint64_t b) {
  asm volatile("{\n.reg .pred p;\nsetp.ne.b32 p, 1, 0;\n"
    "wgmma.mma_async.sync.aligned.m64n24k16.f16.f16.f16 {%0,%1,%2,%3,%4,%5}, {%6,%7,%8,%9}, %10, p, 1, 1, 1;\n}\n"
    : "+r"(d[0]),"+r"(d[1]),"+r"(d[2]),"+r"(d[3]),"+r"(d[4]),"+r"(d[5]) : "r"(a[0]),"r"(a[1]),"r"(a[2]),"r"(a[3]),"l"(b));
}
__device__ __forceinline__ void mma_pv0(uint32_t (&d)[6], const uint32_t (&a)[4], uint64_t b) {
  asm volatile("{\n.reg .pred p;\nsetp.ne.b32 p, 0, 0;\n"
    "wgmma.mma_async.sync.aligned.m64n24k16.f16.f16.f16 {%0,%1,%2,%3,%4,%5}, {%6,%7,%8,%9}, %10, p, 1, 1, 1;\n}\n"
    : "+r"(d[0]),"+r"(d[1]),"+r"(d[2]),"+r"(d[3]),"+r"(d[4]),"+r"(d[5]) : "r"(a[0]),"r"(a[1]),"r"(a[2]),"r"(a[3]),"l"(b));
}
__device__ __forceinline__ void mma_ss_t128(float (&d)[64], uint64_t a, uint64_t b, int acc) {
  asm volatile("{\n.reg .pred p;\nsetp.ne.b32 p, %66, 0;\n"
    "wgmma.mma_async.sync.aligned.m64n128k16.f32.bf16.bf16 {%0,%1,%2,%3,%4,%5,%6,%7,%8,%9,%10,%11,%12,%13,%14,%15,%16,%17,%18,%19,%20,%21,%22,%23,%24,%25,%26,%27,%28,%29,%30,%31,%32,%33,%34,%35,%36,%37,%38,%39,%40,%41,%42,%43,%44,%45,%46,%47,%48,%49,%50,%51,%52,%53,%54,%55,%56,%57,%58,%59,%60,%61,%62,%63}, %64, %65, p, 1, 1, 0, 1;\n}\n"
    : "+f"(d[0]),"+f"(d[1]),"+f"(d[2]),"+f"(d[3]),"+f"(d[4]),"+f"(d[5]),"+f"(d[6]),"+f"(d[7]),"+f"(d[8]),"+f"(d[9]),"+f"(d[10]),"+f"(d[11]),"+f"(d[12]),"+f"(d[13]),"+f"(d[14]),"+f"(d[15]),"+f"(d[16]),"+f"(d[17]),"+f"(d[18]),"+f"(d[19]),"+f"(d[20]),"+f"(d[21]),"+f"(d[22]),"+f"(d[23]),"+f"(d[24]),"+f"(d[25]),"+f"(d[26]),"+f"(d[27]),"+f"(d[28]),"+f"(d[29]),"+f"(d[30]),"+f"(d[31]),"+f"(d[32]),"+f"(d[33]),"+f"(d[34]),"+f"(d[35]),"+f"(d[36]),"+f"(d[37]),"+f"(d[38]),"+f"(d[39]),"+f"(d[40]),"+f"(d[41]),"+f"(d[42]),"+f"(d[43]),"+f"(d[44]),"+f"(d[45]),"+f"(d[46]),"+f"(d[47]),"+f"(d[48]),"+f"(d[49]),"+f"(d[50]),"+f"(d[51]),"+f"(d[52]),"+f"(d[53]),"+f"(d[54]),"+f"(d[55]),"+f"(d[56]),"+f"(d[57]),"+f"(d[58]),"+f"(d[59]),"+f"(d[60]),"+f"(d[61]),"+f"(d[62]),"+f"(d[63]) : "l"(a),"l"(b),"r"(acc));
}
__device__ __forceinline__ void mma_ss_t64(float (&d)[32], uint64_t a, uint64_t b, int acc) {
  asm volatile("{\n.reg .pred p;\nsetp.ne.b32 p, %34, 0;\n"
    "wgmma.mma_async.sync.aligned.m64n64k16.f32.bf16.bf16 {%0,%1,%2,%3,%4,%5,%6,%7,%8,%9,%10,%11,%12,%13,%14,%15,%16,%17,%18,%19,%20,%21,%22,%23,%24,%25,%26,%27,%28,%29,%30,%31}, %32, %33, p, 1, 1, 0, 1;\n}\n"
    : "+f"(d[0]),"+f"(d[1]),"+f"(d[2]),"+f"(d[3]),"+f"(d[4]),"+f"(d[5]),"+f"(d[6]),"+f"(d[7]),"+f"(d[8]),"+f"(d[9]),"+f"(d[10]),"+f"(d[11]),"+f"(d[12]),"+f"(d[13]),"+f"(d[14]),"+f"(d[15]),"+f"(d[16]),"+f"(d[17]),"+f"(d[18]),"+f"(d[19]),"+f"(d[20]),"+f"(d[21]),"+f"(d[22]),"+f"(d[23]),"+f"(d[24]),"+f"(d[25]),"+f"(d[26]),"+f"(d[27]),"+f"(d[28]),"+f"(d[29]),"+f"(d[30]),"+f"(d[31]) : "l"(a),"l"(b),"r"(acc));
}
__device__ __forceinline__ void mma_ss_t24(float (&d)[12], uint64_t a, uint64_t b, int acc) {
  asm volatile("{\n.reg .pred p;\nsetp.ne.b32 p, %14, 0;\n"
    "wgmma.mma_async.sync.aligned.m64n24k16.f32.bf16.bf16 {%0,%1,%2,%3,%4,%5,%6,%7,%8,%9,%10,%11}, %12, %13, p, 1, 1, 0, 1;\n}\n"
    : "+f"(d[0]),"+f"(d[1]),"+f"(d[2]),"+f"(d[3]),"+f"(d[4]),"+f"(d[5]),"+f"(d[6]),"+f"(d[7]),"+f"(d[8]),"+f"(d[9]),"+f"(d[10]),"+f"(d[11]) : "l"(a),"l"(b),"r"(acc));
}

__device__ __forceinline__ uint32_t hfma2(uint32_t a, uint32_t b, uint32_t c) { uint32_t r; asm("fma.rn.f16x2 %0, %1, %2, %3;" : "=r"(r) : "r"(a), "r"(b), "r"(c)); return r; }
__device__ __forceinline__ uint32_t packh(float lo, float hi) { uint32_t r; asm("cvt.rn.f16x2.f32 %0, %1, %2;" : "=r"(r) : "f"(hi), "f"(lo)); return r; }
__device__ __forceinline__ void unpackh(uint32_t a, float& lo, float& hi) { asm("{\n.reg .b16 l, h;\nmov.b32 {l, h}, %2;\ncvt.f32.f16 %0, l;\ncvt.f32.f16 %1, h;\n}" : "=f"(lo), "=f"(hi) : "r"(a)); }
__device__ __forceinline__ uint32_t exp2_mufu(uint32_t s) { uint32_t r; asm("ex2.approx.f16x2 %0, %1;" : "=r"(r) : "r"(s)); return r; }
__device__ __forceinline__ uint32_t exp2_fma(uint32_t s) {
  uint32_t t, u;
  asm("fma.rn.relu.f16x2 %0, %1, %2, %3;" : "=r"(t) : "r"(s), "r"(0x02000200u), "r"(0x000a000au));
  asm("mul.rn.f16x2 %0, %1, %2;" : "=r"(u) : "r"(s), "r"(0x02000200u));
  const uint32_t f = hfma2(u, 0xF800F800u, s);
  const uint32_t y = hfma2(hfma2(f, 0x45614561u, 0x27f627f6u), f, 0x05aa05aau);
  return y + (t << 10);
}
template <int J> __device__ __forceinline__ void sm_unit(const uint32_t (&s)[16], uint32_t (&p)[4]) {
  p[0] = exp2_mufu(s[4 * J]); p[1] = exp2_fma(s[4 * J + 1]); p[2] = exp2_mufu(s[4 * J + 2]); p[3] = exp2_fma(s[4 * J + 3]);
}

#define KD(lo) mk64((lo), dhi(256, 3))
#define VO(x) ((uint32_t)(x) - ((uint32_t)(x) << 16))

__device__ __forceinline__ void flush(uint32_t (&a)[6], uint32_t (&o)[6]) {
#pragma unroll
  for (int i = 0; i < 6; i++) asm volatile("add.rn.f16x2 %0, %0, %1;" : "+r"(a[i]) : "r"(o[i]) : "memory");
}
__device__ __forceinline__ void attn_fast(const uint32_t (&q0)[4], const uint32_t (&q1)[4], uint32_t (&a0)[6], uint32_t (&a1)[6], int lane, int pass) {
  const uint32_t kvfull = sb + B_KVFULL, kvempty = sb + B_KVEMPTY;
  const uint32_t kbase = dlo(sb + KV_OFF, 16), vbase = dlo(sb + KV_OFF, ONES_OFF - KV_OFF);
  uint32_t s0[16] = {}, s1[16] = {}, o0[6] = {}, o1[6] = {};
  pinu(s0); pinu(s1); pinu(o0); pinu(o1);
  {
    uint32_t p0[4]={0,0,0,0}; pinu(p0);
    uint32_t p1[4]={0,0,0,0}; pinu(p1);
    uint32_t p2[4]={0,0,0,0}; pinu(p2);
    uint32_t p3[4]={0,0,0,0}; pinu(p3);
    wg_fence(); mma_qk(s0, q0, KD(kbase)); wg_commit(); wg_wait<0>(); pinu(s0);
    uint32_t vprev = vbase - VO(512);
#pragma unroll 1
    for (int it = 0; it < 8; it++) {
      const uint32_t sA = (it & 1) * 2, phn = ((it + 1) >> 1) & 1;
      const uint32_t kcur = kbase + sA * 512, knxt = kbase + (sA ^ 2) * 512, vcur = vbase + VO(sA * 512);
      wg_fence();
      mma_qk(s1,q1,KD(kcur+0));
      mma_pv0(o1,p2,KD(vprev+VO(960)));
      mma_pv(o1,p3,KD(vprev+VO(992)));
      wg_commit();
      flush(a0, o0);
      sm_unit<0>(s0,p0);
      sm_unit<1>(s0,p1);
      wg_fence();
      mma_pv0(o0,p0,KD(vcur+VO(128)));
      mma_pv(o0,p1,KD(vcur+VO(160)));
      wg_commit();
      wg_wait<1>();
      if (lane==0 && it!=0) mbar_arrive(kvempty+8*((sA^2)+1));
      sm_unit<2>(s0,p2);
      sm_unit<3>(s0,p3);
      wg_fence();
      mma_qk(s0,q0,KD(kcur+256));
      mma_pv(o0,p2,KD(vcur+VO(192)));
      mma_pv(o0,p3,KD(vcur+VO(224)));
      wg_commit();
      wg_wait<1>(); pinu(s1);
      sm_unit<0>(s1,p0);
      sm_unit<1>(s1,p1);
      wg_fence();
      mma_pv(o1,p0,KD(vcur+VO(128)));
      mma_pv(o1,p1,KD(vcur+VO(160)));
      wg_commit();
      wg_wait<1>();
      sm_unit<2>(s1,p2);
      sm_unit<3>(s1,p3);
      wg_fence();
      mma_qk(s1,q1,KD(kcur+256));
      mma_pv(o1,p2,KD(vcur+VO(192)));
      mma_pv(o1,p3,KD(vcur+VO(224)));
      wg_commit();
      wg_wait<1>(); pinu(s0);
      sm_unit<0>(s0,p0);
      sm_unit<1>(s0,p1);
      wg_fence();
      mma_pv(o0,p0,KD(vcur+VO(384)));
      mma_pv(o0,p1,KD(vcur+VO(416)));
      wg_commit();
      wg_wait<1>();
      sm_unit<2>(s0,p2);
      sm_unit<3>(s0,p3);
      if ((it|pass)==0) mbar_wait(kvfull+8, 0);
      wg_fence();
      mma_qk(s0,q0,KD(kcur+512));
      mma_pv(o0,p2,KD(vcur+VO(448)));
      mma_pv(o0,p3,KD(vcur+VO(480)));
      wg_commit();
      wg_wait<1>(); pinu(s1);
      sm_unit<0>(s1,p0);
      sm_unit<1>(s1,p1);
      wg_fence();
      mma_pv(o1,p0,KD(vcur+VO(384)));
      mma_pv(o1,p1,KD(vcur+VO(416)));
      wg_commit();
      wg_wait<1>();
      sm_unit<2>(s1,p2);
      sm_unit<3>(s1,p3);
      wg_fence();
      mma_qk(s1,q1,KD(kcur+512));
      mma_pv(o1,p2,KD(vcur+VO(448)));
      mma_pv(o1,p3,KD(vcur+VO(480)));
      wg_commit();
      wg_wait<1>(); pinu(s0);
      sm_unit<0>(s0,p0);
      sm_unit<1>(s0,p1);
      wg_fence();
      mma_pv(o0,p0,KD(vcur+VO(640)));
      mma_pv(o0,p1,KD(vcur+VO(672)));
      wg_commit();
      wg_wait<1>();
      sm_unit<2>(s0,p2);
      sm_unit<3>(s0,p3);
      wg_fence();
      mma_qk(s0,q0,KD(kcur+768));
      mma_pv(o0,p2,KD(vcur+VO(704)));
      mma_pv(o0,p3,KD(vcur+VO(736)));
      wg_commit();
      wg_wait<1>(); pinu(s1);
      sm_unit<0>(s1,p0);
      sm_unit<1>(s1,p1);
      wg_fence();
      mma_pv(o1,p0,KD(vcur+VO(640)));
      mma_pv(o1,p1,KD(vcur+VO(672)));
      wg_commit();
      wg_wait<1>();
      sm_unit<2>(s1,p2);
      sm_unit<3>(s1,p3);
      wg_fence();
      mma_qk(s1,q1,KD(kcur+768));
      mma_pv(o1,p2,KD(vcur+VO(704)));
      mma_pv(o1,p3,KD(vcur+VO(736)));
      wg_commit();
      wg_wait<1>(); pinu(s0);
      sm_unit<0>(s0,p0);
      sm_unit<1>(s0,p1);
      wg_fence();
      mma_pv(o0,p0,KD(vcur+VO(896)));
      mma_pv(o0,p1,KD(vcur+VO(928)));
      wg_commit();
      wg_wait<1>();
      sm_unit<2>(s0,p2);
      sm_unit<3>(s0,p3);
      mbar_wait(kvfull+8*(sA^2), phn);
      wg_fence();
      mma_qk(s0,q0,KD(knxt));
      mma_pv(o0,p2,KD(vcur+VO(960)));
      mma_pv(o0,p3,KD(vcur+VO(992)));
      wg_commit();
      wg_wait<1>(); pinu(s1);
      sm_unit<0>(s1,p0);
      sm_unit<1>(s1,p1);
      wg_fence();
      mma_pv(o1,p0,KD(vcur+VO(896)));
      mma_pv(o1,p1,KD(vcur+VO(928)));
      wg_commit();
      wg_wait<1>();
      sm_unit<2>(s1,p2);
      sm_unit<3>(s1,p3);
      wg_wait<0>(); pinu(s0); pinu(o0); pinu(o1);
      flush(a1, o1);
      vprev = vcur;
    }
    wg_fence();
    mma_pv0(o1,p2,KD(vprev+VO(960)));
    mma_pv(o1,p3,KD(vprev+VO(992)));
    wg_commit(); flush(a0, o0); wg_wait<0>(); pinu(o1);
    if (lane == 0) mbar_arrive(kvempty + 8 * 3);
    flush(a1, o1);
  }
}

__device__ __forceinline__ void mma16816(float* d, const uint32_t (&a)[4], uint32_t b0, uint32_t b1) {
  asm("mma.sync.aligned.m16n8k16.row.col.f32.bf16.bf16.f32 {%0,%1,%2,%3}, {%4,%5,%6,%7}, {%8,%9}, {%0,%1,%2,%3};"
      : "+f"(d[0]), "+f"(d[1]), "+f"(d[2]), "+f"(d[3]) : "r"(a[0]), "r"(a[1]), "r"(a[2]), "r"(a[3]), "r"(b0), "r"(b1));
}
__device__ __forceinline__ uint32_t trans8(uint32_t a) { uint32_t r; asm("movmatrix.sync.aligned.m8n8.trans.b16 %0, %1;" : "=r"(r) : "r"(a)); return r; }
__device__ __forceinline__ void attn_online(const uint32_t (&qn)[4], float g0, float g1, uint8_t* dst, int pass, int lane) {
  uint32_t q[4];
#pragma unroll
  for (int i = 0; i < 4; i++) {
    const int src = (lane & ~3) | ((2 * lane + (i >> 1)) & 3);
    const uint32_t u = __shfl_sync(~0u, qn[i & 1], src), v = __shfl_sync(~0u, qn[2 + (i & 1)], src);
    q[i] = (lane & 2) ? v : u;
  }
  float o[12] = {};
  float m0 = -3e38f, m1 = -3e38f;
#pragma unroll 2
  for (int b = 0; b < 128; b++) {
    const uint4 k = __ldcg(g_kvb + b * 64 + lane), v = __ldcg(g_kvb + b * 64 + 32 + lane);
    float s[8] = {};
    mma16816(s, q, k.x, k.z); mma16816(s + 4, q, k.y, k.w);
    float x = fmaxf(fmaxf(m0, fmaxf(s[0], s[1])), fmaxf(s[4], s[5])), y = fmaxf(fmaxf(m1, fmaxf(s[2], s[3])), fmaxf(s[6], s[7]));
    x = fmaxf(x, __shfl_xor_sync(~0u, x, 1)); x = fmaxf(x, __shfl_xor_sync(~0u, x, 2));
    y = fmaxf(y, __shfl_xor_sync(~0u, y, 1)); y = fmaxf(y, __shfl_xor_sync(~0u, y, 2));
    const float cx = ex2((m0 - x) * QS), cy = ex2((m1 - y) * QS);
    m0 = x; m1 = y;
#pragma unroll
    for (int j = 0; j < 3; j++) { o[4 * j] *= cx; o[4 * j + 1] *= cx; o[4 * j + 2] *= cy; o[4 * j + 3] *= cy; }
    const uint32_t p[4] = {pack2(ex2((s[0] - x) * QS), ex2((s[1] - x) * QS)), pack2(ex2((s[2] - y) * QS), ex2((s[3] - y) * QS)),
                           pack2(ex2((s[4] - x) * QS), ex2((s[5] - x) * QS)), pack2(ex2((s[6] - y) * QS), ex2((s[7] - y) * QS))};
    mma16816(o, p, trans8(v.x), trans8(v.y)); mma16816(o + 4, p, trans8(v.z), trans8(v.w)); mma16816(o + 8, p, 0x3F803F80u, 0x3F803F80u);
  }
  const float a = __fdividef(g0, o[8]), b = __fdividef(g1, o[10]);
  const uint32_t w0 = pack2(o[0] * a, o[1] * a), w1 = pack2(o[2] * b, o[3] * b), w2 = pack2(o[4] * a, o[5] * a), w3 = pack2(o[6] * b, o[7] * b);
  if (pass == 0) {
    dst += (lane & 2) * 508 + (lane & 1) * 4;
    stg64(dst, w0, w2); stg64(dst + 128, w1, w3);
  } else {
    dst += (lane & 1) * 16 - (lane & 2) * 12;
    st_rlx64(dst, ~w0, ~w1); st_rlx64(dst + 16, ~w2, ~w3);
  }
}

__device__ __forceinline__ void store_o(const float (&o)[12], float g0, float g1, uint8_t* dst, int pass) {
  const float a = __fdividef(g0, o[8]), b = __fdividef(g1, o[10]);
  const uint32_t w0 = pack2(o[0] * a, o[1] * a), w1 = pack2(o[2] * b, o[3] * b), w2 = pack2(o[4] * a, o[5] * a), w3 = pack2(o[6] * b, o[7] * b);
  if (pass == 0) { stg32(dst, w0); stg32(dst + 128, w1); stg32(dst + 1024, w2); stg32(dst + 1152, w3); }
  else st_rlx128(dst, ~w0, ~w1, ~w2, ~w3);
}

__device__ __forceinline__ void attn_passes(uint32_t (&qh)[4][4], uint32_t (&qb)[4][4], float qn, uint8_t* odst, int wg, uint32_t (&r)[8][4], const uint8_t* src) {
  const int lane = threadIdx.x & 31;
  float g0 = 0.f, g1 = 0.f;
#pragma unroll 1
  for (int p = 0; p < 2; p++) {
    {
      uint32_t a0[6] = {}, a1[6] = {};
      attn_fast(qh[0], qh[1], a0, a1, lane, p);
      {
        uint32_t go;
        asm volatile("{\n.reg .pred p;\nmbarrier.test_wait.parity.shared::cta.b64 p, [%1], 0;\nselp.u32 %0, 1, 0, p;\n}" : "=r"(go) : "r"(sb + B_TAIL) : "memory");
#pragma unroll
        for (int j = 0; j < 8; j++) ld_rlx128(r[j], src + j * 512, PRE && go);
      }
      if (p == 0) {
        mbar_wait(sb + B_GREADY, 0);
        const uint32_t ga = sb + G_OFF + ((threadIdx.x >> 5) * 16 + (lane >> 2)) * 8;
        g0 = __uint_as_float(lds32(ga)); g1 = __uint_as_float(lds32(ga + 64));
        const float kn = __uint_as_float(lds32(sb + MISC_OFF + 32));
        qn = !FORCE_SLOW && qn * kn <= 372.f && qn <= 65536.f && kn <= 65536.f ? 128.f : NAN;
      }
      float o0[12], o1[12], hi = 0.f;
#pragma unroll
      for (int i = 0; i < 6; i++) { unpackh(a0[i], o0[2 * i], o0[2 * i + 1]); unpackh(a1[i], o1[2 * i], o1[2 * i + 1]); }
      const float lo = fminf(fminf(o0[8], o0[10]), fminf(o1[8], o1[10]));
#pragma unroll
      for (int i = 0; i < 11; i++) hi += fabsf(o0[i]) + fabsf(o1[i]);
      const bool ok = lo >= qn && hi < INFINITY;
      if (__all_sync(~0u, ok)) {
        store_o(o0, g0, g1, odst, p);
        store_o(o1, g0, g1, odst + 2048, p);
      } else {
#pragma unroll 1
        for (int h = 0; h < 2; h++) {
          attn_online(qb[0], g0, g1, odst + h * 2048, p, lane);
#pragma unroll
          for (int i = 0; i < 4; i++) qb[0][i] = qb[1][i];
        }
      }
    }
    if (p == 0) {
      odst += 32768 + (threadIdx.x & 96) * 8 + lane * 12;
      st_rlx128(odst, 0, 0, 0, 0); st_rlx128(odst + 2048, 0, 0, 0, 0);
      __syncwarp();
      if (lane == 0) mbar_arrive(sb + B_PUB + 32);
    }
#pragma unroll
    for (int i = 0; i < 4; i++) { qh[0][i] = qh[2][i]; qh[1][i] = qh[3][i]; qb[0][i] = qb[2][i]; qb[1][i] = qb[3][i]; }
  }
}

__device__ __forceinline__ uint32_t o_off(int c) { return sb + (c >> 1) * FST + (c & 1) * 4096; }
__device__ __forceinline__ void o_push(int c, int lane) {
  asm volatile("fence.proxy.async.shared::cta;" ::: "memory");
  __syncwarp();
  if (lane == 0) {
    uint32_t old;
    asm volatile("atom.shared.or.b32 %0, [%1], %2;" : "=r"(old) : "r"(sb + MISC_OFF + 40), "r"(1u << c) : "memory");
    if (!(old >> c & 1)) {
      const int pos = __popc(old);
      sts32(sb + MISC_OFF + 4 * pos, dlo(o_off(c), 1024));
      mbar_arrive(sb + B_Q + 8 * pos);
    }
  }
}

__device__ __forceinline__ float geglu(float x, float u) {
  const float y = x * fmaf(x * x, 0.044715f * 0.7978845608028654f, 0.7978845608028654f);
  float t; asm("tanh.approx.f32 %0, %1;" : "=f"(t) : "f"(y));
  const float h = x * u;
  return fmaf(h, t, h);
}
template <int N> __device__ __forceinline__ void store_h(const float (&d)[N], uint8_t* dst) {
#pragma unroll
  for (int j = 0; j < N / 8; j++) {
    stg32(dst + j * 1024, pack2(geglu(d[4 * j], d[N / 2 + 4 * j]), geglu(d[4 * j + 1], d[N / 2 + 1 + 4 * j])));
    stg32(dst + j * 1024 + 128, pack2(geglu(d[4 * j + 2], d[N / 2 + 2 + 4 * j]), geglu(d[4 * j + 3], d[N / 2 + 3 + 4 * j])));
  }
}

__device__ __forceinline__ int h_slot(int c, int u) {
  const int late = 27 - ((u >> 3) % 3);
  return c == 27 ? late : c == late ? 27 : c;
}
__device__ __forceinline__ void helper_cta(const Maps& mp, int warp, int lane) {
  const int v0 = (blockIdx.x - 128) * 24, isw = 32 - (v0 & 31);
  constexpr uint32_t HW = sb + B_XFULL, HF = sb + B_FFULL, HE = sb + B_FEMPTY, HP = sb + G_OFF;
  if (warp == 1 && lane < 3) asm volatile("prefetch.tensormap [%0];" ::"l"(lane == 0 ? &mp.x : lane == 1 ? &mp.wg : &mp.wu) : "memory");
  if (threadIdx.x < 24) {
    const int i = threadIdx.x;
    if (i < 8) { mbar_init(HW + 8 * i, 1); mbar_init(HF + 8 * i, 1); mbar_init(HE + 8 * i, 4); }
    mbar_init(HP + 8 * i, 4);
    asm volatile("fence.mbarrier_init.release.cluster;" ::: "memory");
  }
  __syncthreads();
  if (warp == 12) {
#pragma unroll 1
    for (int m = 0, s = 0, ph = 1; m < 99; m++) {
      mbar_wait(HE + 8 * s, ph);
      const int i = (m >> 2) - (~m & 1), j = ((m >> 1) & 1) + 2 * (~m & 1);
      if ((unsigned)i < 24) u_tma3d(HF + 8 * s, 16384, sb + W_OFF + s * 16384, &mp.x, 0, ((v0 + i) & 31) * 64, 2 * j);
      else if (lane < 5) mbar_arrive((lane < 4 ? HE : HF) + 8 * s);
      __syncwarp();
      const int e = m < 6 ? m + (m == 5) : m - 4 * isw - 2;
      if (e == 1 || e == 3 || e == 4 || e == 6) {
        const int hc = 25 + (v0 >> 5) + (m >= 6);
        for (int k = e & 6; k < (e & 6) + 2; k++) u_tma2d_pair(HW + 8 * k, sb + k * 16384, &mp.wg, &mp.wu, hc * 64, k * 64, k * 64);
      }
      if (++s == 6) { s = 0; ph ^= 1; }
    }
  } else if (warp == 13) {
#pragma unroll 1
    for (int i = 0; i < 24; i++) {
      mbar_wait_ns<HNP>(HP + 8 * i, 0);
      fence_gpu();
      if (lane == 0) { st_rlx(g_flags + 64 + ((v0 + i) & 31) * 64 + 2 * h_slot(25 + ((v0 + i) >> 5), (v0 + i) & 31), 1); EV(i); }
    }
  } else if (warp < 12) {
    constexpr uint32_t H128 = dhi(1024, 1);
    const uint32_t xl = dlo(sb + W_OFF, 16), wl = dlo(sb, 8192);
    const int w = warp >> 2;
    float d[64];
    zero(d);
#pragma unroll 1
    for (int i = w; i < 24; i += 3) {
      const int u = (v0 + i) & 31, hc = h_slot(25 + ((v0 + i) >> 5), u);
      if (i) asm volatile("bar.sync %0, 256;" ::"r"(1 + w) : "memory");
      int sp = 0;
#pragma unroll 1
      for (int j = 0; j < 4; j++) {
        const int m = 4 * i + 2 * j + (j < 2), s = m % 6;
        if (i < 3 || (unsigned)(i - isw) < 3) { mbar_wait(HW + 16 * j, i >= isw); mbar_wait(HW + 16 * j + 8, i >= isw); }
        mbar_wait(HF + 8 * s, (m / 6) & 1);
        wg_fence();
#pragma unroll
        for (int k = 0; k < 8; k++) mma_ss_t128(d, mk64(xl + s * 1024 + (k >> 2) * 512 + 2 * (k & 3), H128), mk64(wl + (2 * j + (k >> 2)) * 1024 + 128 * (k & 3), H128), (j | k) != 0);
        wg_commit();
        wg_wait<1>();
        if (j == 1 && i != 23) asm volatile("bar.arrive %0, 256;" ::"r"(w == 2 ? 1 : 2 + w) : "memory");
        if (j && lane == 0) mbar_arrive(HE + 8 * sp);
        sp = s;
      }
      wg_wait<0>();
      if (lane == 0) mbar_arrive(HE + 8 * sp);
      mbar_wait(HF + 56, 1);
      pin(d);
      store_h(d, g_a + (size_t)u * A_BYTES + hc * 8192 + (warp & 3) * 256 + lane * 4);
      __syncwarp();
      if (lane == 0) mbar_arrive(HP + 8 * i);
      pin(d);
    }
  }
}

__global__ void __launch_bounds__(512, 1)
fused_kernel(const __grid_constant__ Maps mp, const uint16_t* __restrict__ gate_w, const uint4* __restrict__ wk, const uint4* __restrict__ wv,
             const uint8_t* __restrict__ wd_raw, const uint8_t* __restrict__ wo_raw, uint4* __restrict__ out) {
  extern __shared__ __align__(1024) uint8_t smem[];
  const int tid = threadIdx.x, lane = tid & 31;
  const int warp = __shfl_sync(~0u, tid >> 5, 0);
  const int wg = warp >> 2, wq4 = warp & 3;
  const int tb = blockIdx.x >> 3, cg = blockIdx.x & 7;
  const int half = cg & 1;
  if (blockIdx.x >= 128) { helper_cta(mp, warp, lane); return; }
  const bool skip3 = cg < 4;

  if (warp == 12) {
    if (lane == 0) {
      EV(0);
      if ((uint32_t)__cvta_generic_to_shared(smem) != sb) __trap();
      for (int i = 0; i < 8; i++) mbar_init(sb + B_XFULL + 8 * i, 1);
      for (int i = 0; i < 4; i++) mbar_init(sb + B_WQ + 8 * i, 1);
      asm volatile("fence.mbarrier_init.release.cluster;" ::: "memory");
    }
    __syncwarp();
    const uint32_t xb = sb + B_XFULL + 32 * half, xd = sb + X_OFF + half * 65536;
    const int row = tb * 128 + half * 64;
    if (cg < 4) {
#pragma unroll
      for (int j = 0; j < 4; j++) u_tma3d(xb + 8 * j, 16384, xd + j * 16384, &mp.x, 0, row, 2 * j);
    }
#pragma unroll
    for (int j = 0; j < 4; j++) {
      u_tma2d(sb + B_WQ + 8 * j, 16384, sb + W_OFF + j * 16384, &mp.wq, cg * 64, j * 128);
      u_tma3d((xb ^ 32) + 8 * j, 16384, (xd ^ 65536) + j * 16384, &mp.x, 0, row ^ 64, 2 * j);
      if (cg >= 4) u_tma3d(xb + 8 * j, 16384, xd + j * 16384, &mp.x, 0, row, 2 * j);
    }
  } else if (tid == 416) {
    mbar_init(sb + B_GREADY, 1); mbar_init(sb + B_FFN1, 4);
    for (int i = 0; i < 4; i++) { mbar_init(sb + B_WFULL + 8 * i, 1); mbar_init(sb + B_WEMPTY + 8 * i, 8); mbar_init(sb + B_KVFULL + 8 * i, 1); mbar_init(sb + B_KVEMPTY + 8 * i, 8); mbar_init(sb + B_PUB + 8 * i, 4); }
    mbar_init(sb + B_PUB + 32, 8);
    for (int i = 0; i < 8; i++) { mbar_init(sb + B_FFULL + 8 * i, 2); mbar_init(sb + B_FEMPTY + 8 * i, 4); mbar_init(sb + B_Q + 8 * i, 1); }
    mbar_init(sb + B_TAIL, 4); sts32(sb + MISC_OFF + 40, 0);
    asm volatile("fence.mbarrier_init.release.cluster;" ::: "memory");
  } else if (tid == 448) {
    asm volatile("prefetch.tensormap [%0];" ::"l"(&mp.wg) : "memory");
    asm volatile("prefetch.tensormap [%0];" ::"l"(&mp.wu) : "memory");
    asm volatile("prefetch.tensormap [%0];" ::"l"(&mp.wd) : "memory");
    asm volatile("prefetch.tensormap [%0];" ::"l"(&mp.wo) : "memory");
    asm volatile("prefetch.tensormap [%0];" ::"l"(&mp.wg2) : "memory");
    asm volatile("prefetch.tensormap [%0];" ::"l"(&mp.wu2) : "memory");
  }
  uint4 wa[4], wb[4];
  uint32_t wz[4];
  if (cg < 4 && wg == 2) {
    const uint4* w = (cg < 2 ? wk : wv) + (tid & 127) * 2;
#pragma unroll
    for (int i = 0; i < 4; i++) { wa[i] = __ldg(w + i * 256); wb[i] = __ldg(w + i * 256 + 1); wz[i] = __ldg(gate_w + (tid & 127) + i * 128); }
  }
  if (tid < 128) { sts32(sb + ONES_OFF + tid * 4, 0x3C003C00u); asm volatile("fence.proxy.async.shared::cta;" ::: "memory"); }
  __syncthreads();
  if (tid == 0) EV(1);

  uint8_t* const a_tb = g_a + (size_t)(tb * 2) * A_BYTES;
  uint32_t* const fl_tb = g_flags + 64 + tb * 128;

  if (wg == 3) {
    asm volatile("setmaxnreg.dec.sync.aligned.u32 %0;" ::"n"(REG_PROD));
    if (wq4 == 1 || wq4 == 2) {
      if (cg < 4) asm volatile("bar.sync 4, 224;" ::: "memory");
      else mbar_wait_sleep<NS_W>(sb + B_XFULL + 16, 0);
    }
    if (wq4 == 0) {
#pragma unroll 1
      for (int n = 0; n < (skip3 ? 24 : 28); n++) {
        const int s = n & 3;
        const int c0 = n < 24 ? ((n & 24) + cg) * 64 : 24 * 64 + (cg & 2) * 16, c1 = n < 24 ? (n & 7) * 64 : s * 128;
        mbar_wait_sleep<NS_W>(sb + B_WEMPTY + 8 * s, (n >> 2) & 1);
        u_tma2d_pair(sb + B_WFULL + 8 * s, sb + W_OFF + s * 16384, n < 24 ? &mp.wg : &mp.wg2, n < 24 ? &mp.wu : &mp.wu2, c0, c1, c1);
        if (n == 8) { u_prefetch(wd_raw + blockIdx.x * 14336, 14336); u_prefetch(wo_raw + blockIdx.x * 4096, 4096); }
      }
      mbar_wait_sleep<NS_W>(sb + B_FFN1, 0);
#pragma unroll 1
      for (int n = 0; n < 36; n++) {
        const int s = n & 7;
        mbar_wait_sleep<NS_W>(sb + B_FEMPTY + 8 * s, ((n >> 3) & 1) ^ 1);
        u_tma4d(sb + B_FFULL + 8 * s, 16384, sb + s * FST + 8192, n < 28 ? &mp.wd : &mp.wo, n & 32, n < 28 ? 2 * h_slot(n, 2 * tb) : 2 * (n & 3), cg & 6);
        if (n >= 32 && lane == 0) mbar_arrive(sb + B_FFULL + 8 * s);
      }
    } else if (wq4 == 1) {
      uint32_t todo = 0x11111111u ^ (1u << 2 * (tb & 14)), rdy = 0;
#pragma unroll 1
      for (int n = 2; n < 33; n += 2) {
        if (n == 14 ? rdy != 0x11111111u : !(rdy & todo)) {
          for (int i = 0; n == 14 ? rdy != 0x11111111u : !(rdy & todo); i++) {
            const uint64_t f = ld_acq64(g_flags + 2 * lane);
            rdy = __ballot_sync(~0u, (uint32_t)f & (uint32_t)(f >> 32) & 1);
            rdy &= rdy >> 1; rdy &= (rdy >> 2) & 0x11111111u;
            if (i > 0x100000) __trap();
          }
          fence_async_gl();
        }
        const int c = __ffs(rdy & todo) - 1, s = n & 3;
        todo ^= 1u << c;
        if (!todo) todo = 0x11111111u;
        mbar_wait_sleep<NS_KV>(sb + B_KVEMPTY + 8 * (s + 1), ((n >> 2) & 1) ^ 1);
        u_bulk(sb + B_KVFULL + 8 * s, 16384, sb + KV_OFF + s * 8192, g_kv + c * 4096);
      }
    } else if (wq4 == 3) {
      if (cg < 4) {
        uint32_t* const fl = g_flags + (tb * 2 + half) * 2 + (cg >> 1);
        asm volatile("bar.sync 4, 224;" ::: "memory");
        fence_gpu();
        if (lane == 0) { st_rlx(fl, 1); EV(2); }
        asm volatile("bar.sync 5, 160;" ::: "memory");
        const uint32_t m = __reduce_max_sync(~0u, lds32(sb + MISC_OFF + 48 + (lane & 3) * 4));
        fence_gpu();
        if (lane == 0) st_rlx(fl, m | 3);
      }
#pragma unroll 1
      for (int e = 0; e < 5; e++) {
        if (e == 3 && skip3) continue;
        mbar_wait_sleep<NS_W>(sb + B_PUB + 8 * e, 0);
        fence_gpu();
        const int idx = e < 3 ? 2 * (e * 8 + cg) : e == 3 ? 48 + (cg & 2) * 4 : 2 * cg + 1;
        if (lane < 2 && (e != 3 || lane == half)) st_rlx(fl_tb + lane * 64 + idx, 1);
      }
    } else {
      {
        mbar_wait_sleep<NS_W>(sb + B_KVEMPTY + 8 * GSL, 0);
        uint64_t f;
        for (int i = 0;; i++) {
          f = ld_acq64(g_flags + 2 * lane);
          if (__all_sync(~0u, (uint32_t)f & (uint32_t)(f >> 32) & 2)) break;
          if (i > 0x100000) __trap();
          __nanosleep(NS_F);
        }
        fence_async_gl();
        const uint32_t fk = __reduce_max_sync(~0u, max((uint32_t)f, (uint32_t)(f >> 32)));
        if (lane == 0) sts32(sb + MISC_OFF + 32, fk);
        __syncwarp();
        u_bulk(sb + B_GREADY, 1024, sb + G_OFF, g_gate + tb * 128);
      }
      mbar_wait_sleep<NS_W>(sb + B_FFN1, 0);
      const uint32_t* fl = fl_tb + half * 64 + 2 * lane;
      const uint8_t* src = a_tb + half * A_BYTES;
      int ready = 0;
#pragma unroll 1
      for (int t = 0; t < 32; t++) {
        const int n = t < 27 ? t : t < 31 ? t + 1 : 27;
        if (t >= ready) {
          for (int i = 0;; i++) {
            const uint64_t f = ld_acq64(fl);
            const uint32_t rh = __ballot_sync(~0u, (uint32_t)f != 0), ro = __ballot_sync(~0u, (f >> 32) != 0);
            ready = __ffs(~(rh & ((rh >> 4) | ~(1u << 24)) & 0x7ffffffu)) - 1;
            if (ready == 27) ready += (__ffs(~ro) - 1) >> 1;
            if (ready == 31) ready += rh >> 27 & 1;
            if (t < ready) break;
            if (i > 0x100000) __trap();
            __nanosleep(NS_F);
          }
          fence_async_gl();
        }
        const int s = n & 7;
        mbar_wait_sleep<NS_W>(sb + B_FEMPTY + 8 * s, ((n >> 3) & 1) ^ 1);
        u_bulk(sb + B_FFULL + 8 * s, 8192, sb + s * FST, src + n * 8192);
      }
      if (cg < 4) {
        for (int i = 0; !__all_sync(~0u, ld_acq(g_flags + 64 + (tb ^ 1) * 128 + 2 * (lane & 7))); i++) if (i > 0x100000) __trap();
        for (int i = 0; i < 4; i++) g_kv0[tb * 512 + cg * 128 + i * 32 + lane] = make_uint4(0, 0, 0, 0);
      }
      uint32_t last = 0;
      if (lane == 0) { __threadfence(); last = atomicAdd(&g_done, 1) == 127; __threadfence(); }
      if (__shfl_sync(~0u, last, 0)) {
        for (int i = lane; i < (64 + 32 * 64) / 4; i += 32) reinterpret_cast<uint4*>(g_flags)[i] = make_uint4(0, 0, 0, 0);
        if (lane == 0) g_done = 0;
      }
    }
  } else if (wg == 2) {
    asm volatile("setmaxnreg.inc.sync.aligned.u32 %0;" ::"n"(REG_GEMM));
    constexpr uint32_t H128 = dhi(1024, 1);
    float e[11] = {};
    if (cg < 4) {
#pragma unroll
      for (int i = 0; i < 4; i++) {
        const uint32_t a = sb + KV_OFF + i * 4096 + (tid & 127) * 32 + (tid & 4) * 4;
        sts128(a, wa[i].x, wa[i].z, wb[i].x, wb[i].z); sts128(a ^ 16, wa[i].y, wa[i].w, wb[i].y, wb[i].w); sts32(a + 16384, wz[i]);
      }
      asm volatile("fence.proxy.async.shared::cta;" ::: "memory");
      float d[12];
      zero(d);
      bar_sync(3);
      const uint32_t xl = dlo(sb + X_OFF + half * 65536, 16), wl = dlo(sb + KV_OFF, 16384);
#pragma unroll 1
      for (int j = 0; j < 4; j++) {
        mbar_wait(sb + B_XFULL + 32 * half + 8 * j, 0);
        wg_fence();
#pragma unroll
        for (int k = 0; k < 8; k++) mma_ss_t24(d, mk64(xl + j * 1024 + (k >> 2) * 512 + 2 * (k & 3), H128), KD(wl + j * 256 + 32 * k), 1);
        wg_commit();
      }
      wg_wait<0>(); pin(d);
      if ((tid & 127) == 0) EV(46);
      const float sc = cg < 2 ? 0.0625f : 1.f;
      const uint32_t w0 = packh(d[0] * sc, d[1] * sc), w1 = packh(d[4] * sc, d[5] * sc), w2 = packh(d[2] * sc, d[3] * sc), w3 = packh(d[6] * sc, d[7] * sc);
      st_rlx128(g_kv0 + tb * 512 + cg * 128 + (tid & 127), ~w0, ~w1, ~w2, ~w3);
      uint8_t* dst = g_kv + (tb * 2 + half) * 4096 + (cg >> 1) * 2048 + wq4 * 512 + ((lane * 8) ^ (lane & 16));
      stg64(dst, w0, w1); stg64(dst + 256, w2, w3);
      asm volatile("bar.arrive 4, 224;" ::: "memory");
      if ((tid & 127) == 0) EV(47);
#pragma unroll
      for (int i = 0; i < 11; i++) asm volatile("mov.b32 %0, %1;" : "=f"(e[i]) : "f"(d[i]));
    }
    {
      uint32_t r[8][4] = {}, pend = 255;
      const uint32_t a = sb + KV_OFF + wq4 * 512 + ((lane * 8) ^ (lane & 16));
#pragma unroll
      for (int h = 0; h < 2; h++) {
#pragma unroll 1
        for (int i = 0; i < 0x100000; i++) {
#pragma unroll
          for (int j = 4 * h; j < 4 * h + 4; j++) if (__all_sync(~0u, min(min(r[j][0], r[j][1]), min(r[j][2], r[j][3])) != 0)) pend &= ~(1u << j);
          if (!(pend & (15 << 4 * h))) break;
#pragma unroll
          for (int j = 4 * h; j < 4 * h + 4; j++) if (pend >> j & 1) ld_rlx128(r[j], g_kv0 + (tb ^ h) * 512 + (j & 3) * 128 + (tid & 127), 1);
        }
        if (h == 0 && cg < 4) bar_sync(3);
#pragma unroll
        for (int j = 4 * h; j < 4 * h + 4; j++) {
          const uint32_t b = a + h * 8192 + (j & 1) * 4096 + (j & 2) * 1024;
          sts64(b, ~r[j][0], ~r[j][1]); sts64(b + 256, ~r[j][2], ~r[j][3]);
        }
        asm volatile("fence.proxy.async.shared::cta;" ::: "memory");
        if (h == 0) {
#pragma unroll
          for (int j = 4; j < 8; j++) ld_rlx128(r[j], g_kv0 + (tb ^ 1) * 512 + (j & 3) * 128 + (tid & 127), 1);
        }
        bar_sync(3);
        if (tid == 256) { mbar_arrive(sb + B_KVFULL + 8 * h); EV(h ? 53 : 45); }
        if (h == 1 && cg < 4) {
          g_kvb[(tb * 8 + half * 4 + wq4) * 64 + (cg >> 1) * 32 + lane] = make_uint4(pack2(e[0], e[1]), pack2(e[2], e[3]), pack2(e[4], e[5]), pack2(e[6], e[7]));
          uint32_t mx;
          if (cg < 2) {
            const float z0 = __shfl_sync(~0u, e[8], (lane & 7) * 4), z1 = __shfl_sync(~0u, e[10], (lane & 7) * 4);
            const float g = 1.f / (1.f + __expf((lane & 8) ? -z1 : -z0));
            if (lane < 16) g_gate[tb * 128 + half * 64 + wq4 * 16 + lane] = make_float2(g, 0.5f * (1.f - g));
            float n0 = sq4(e[0], e[1], e[4], e[5]), n1 = sq4(e[2], e[3], e[6], e[7]);
            n0 += __shfl_xor_sync(~0u, n0, 1); n1 += __shfl_xor_sync(~0u, n1, 1);
            n0 += __shfl_xor_sync(~0u, n0, 2); n1 += __shfl_xor_sync(~0u, n1, 2);
            mx = __reduce_max_sync(~0u, max(__float_as_uint(n0), __float_as_uint(n1)));
          } else {
            bool ok = true;
#pragma unroll
            for (int i = 0; i < 4; i++) {
              const int j = (i & 1) + (i >> 1) * 4;
              uint32_t c = max(__float_as_uint(e[j]) & 0x7fffffffu, __float_as_uint(e[j + 2]) & 0x7fffffffu);
              c = max(c, __shfl_xor_sync(~0u, c, 4)); c = max(c, __shfl_xor_sync(~0u, c, 8)); c = max(c, __shfl_xor_sync(~0u, c, 16));
              ok = ok && (c == 0 || (c >= 0x37800000u && c <= 0x47000000u));
            }
            mx = __all_sync(~0u, ok) ? 0 : 0x7f800001u;
          }
          if (lane == 0) sts32(sb + MISC_OFF + 48 + wq4 * 4, mx);
          asm volatile("bar.arrive 5, 160;" ::: "memory");
          if ((tid & 127) == 0) EV(52);
        }
      }
    }
    float d0[64], d1[64];
    zero(d0); zero(d1);
    if (QFIRST) mbar_wait(sb + B_WEMPTY + 24, 0);
    const uint32_t xl = dlo(sb + X_OFF, 16), wl = dlo(sb + W_OFF, 8192);
    uint8_t* const hdst = a_tb + wq4 * 256 + lane * 4;
    const uint32_t grow = sb + G_OFF + (wq4 * 16 + (lane >> 2)) * 8 + 4;
#pragma unroll 1
    for (int st = 0; st < 3; st++) {
#pragma unroll 1
      for (int kc = 0; kc < 8; kc++) {
        const int s = kc & 3;
        if (!QFIRST && st == 0) { mbar_wait(sb + B_XFULL + 8 * (kc >> 1), 0); mbar_wait(sb + B_XFULL + 32 + 8 * (kc >> 1), 0); }
        mbar_wait(sb + B_WFULL + 8 * s, (kc >> 2) & 1);
        const uint32_t a = xl + kc * 512, b = wl + s * 1024;
#pragma unroll
        for (int k = 0; k < 4; k++) {
          wg_fence();
          mma_ss_t128(d0, mk64(a + 2 * k, H128), mk64(b + 128 * k, H128), (kc | k) != 0);
          mma_ss_t128(d1, mk64(a + 4096 + 2 * k, H128), mk64(b + 128 * k, H128), (kc | k) != 0);
          wg_commit(); wg_wait<GW1>();
          if (GW1 && k == 0 && kc != 0 && lane == 0) mbar_arrive2(sb + B_WEMPTY + 8 * ((s + 3) & 3));
        }
        if (!GW1 && lane == 0) mbar_arrive2(sb + B_WEMPTY + 8 * s);
      }
      if (GW1) { wg_wait<0>(); if (lane == 0) mbar_arrive2(sb + B_WEMPTY + 8 * 3); }
      pin(d0); pin(d1);
      if (st == 2 && skip3 && lane == 0) mbar_arrive(sb + B_FFN1);
      if (st == 0 && tid == 256) EV(8);
      if (st == 0) mbar_wait(sb + B_GREADY, 0);
      const int hc = st * 8 + cg;
      store_h(d0, hdst + hc * 8192);
      store_h(d1, hdst + A_BYTES + hc * 8192);
      __syncwarp();
      if (lane == 0) mbar_arrive(sb + B_PUB + 8 * st);
      pin(d0); pin(d1);
    }
    if (!skip3) {
      float d2[32];
      zero(d2);
#pragma unroll 1
      for (int s = 0; s < 4; s++) {
        mbar_wait(sb + B_WFULL + 8 * s, 0);
        const uint32_t a = xl + s * 1024 + half * 4096, b = wl + s * 1024;
#pragma unroll
        for (int k = 0; k < 8; k += S3K) {
          wg_fence();
#pragma unroll
          for (int i = k; i < k + S3K; i++) mma_ss_t64(d2, mk64(a + (i >> 2) * 512 + 2 * (i & 3), H128), mk64(b + 64 * i, dhi(512, 2)), 1);
          wg_commit(); wg_wait<0>();
        }
      }
      pin(d2);
      if (lane == 0) mbar_arrive(sb + B_FFN1);
      if (tid == 256) EV(12);
      store_h(d2, hdst + half * A_BYTES + 24 * 8192 + (cg & 2) * 2048);
      __syncwarp();
      if (lane == 0) mbar_arrive(sb + B_PUB + 24);
    }
    const uint32_t al = dlo(sb, 1024), bl = dlo(sb + 8192, 8192);
    constexpr uint32_t HA = dhi(128, 0);
    auto fin = [&](int n0, int n1) {
#pragma unroll 1
      for (int n = n0; n < n1; n++) {
        const int s = n & 7;
        mbar_wait_sleep<NS_G>(sb + B_FFULL + 8 * s, (n >> 3) & 1);
        const uint32_t a = al + s * (FST >> 4), b = bl + s * (FST >> 4);
#pragma unroll
        for (int k = 0; k < 4; k += 2) {
          wg_fence();
#pragma unroll
          for (int i = k; i < k + 2; i++) mma_ss_t128(d0, mk64(a + 128 * i, HA), mk64(b + 128 * i, H128), n0 != 0 || (n | i) != 0);
          wg_commit(); wg_wait<1>();
          if (n0 == 0 && k == 0 && n != 0 && lane == 0) mbar_arrive(sb + B_FEMPTY + 8 * ((s + 7) & 7));
        }
      }
    };
    fin(0, 28);
    wg_wait<0>();
    pin(d0);
    if (lane == 0) { mbar_arrive(sb + B_FEMPTY + 24); mbar_arrive(sb + B_TAIL); }
    {
      const float c0 = __uint_as_float(lds32(grow + half * 512)), c1 = __uint_as_float(lds32(grow + half * 512 + 64));
#pragma unroll
      for (int i = 0; i < 64; i++) d0[i] *= (i & 2) ? c1 : c0;
    }
    pin(d0);
    fin(28, 32);
    if (tid == 256) EV(18);
#pragma unroll
    for (int s = 0; s < 4; s++) mbar_wait(sb + B_FFULL + 8 * s, 0);
    if (tid == 256) EV(31);
#pragma unroll 1
    for (int n = 0; n < 8; n++) {
      mbar_wait(sb + B_Q + 8 * n, 0);
      const uint32_t a = lds32(sb + MISC_OFF + 4 * n);
      wg_fence();
      mma_ss_t128(d0, mk64(a, HA), mk64(a + (bl - al), H128), 1);
      mma_ss_t128(d0, mk64(a + 128, HA), mk64(a + (bl - al) + 128, H128), 1);
      wg_commit();
    }
    wg_wait<0>();
    pin(d0);
    if (tid == 256) EV(19);
    const uint32_t stg = sb + 4 * FST + wq4 * 256;
#pragma unroll
    for (int j = 0; j < 8; j++) {
      const int c = (2 * j + (lane >> 4)) & 7;
      stsm4(stg + (j >> 2) * FST + c * 1024 + ((lane & 15) ^ c) * 16, pack2(d0[8 * j], d0[8 * j + 1]), pack2(d0[8 * j + 2], d0[8 * j + 3]), pack2(d0[8 * j + 4], d0[8 * j + 5]), pack2(d0[8 * j + 6], d0[8 * j + 7]));
    }
    __syncwarp();
    uint4* const op = out + (tb * 128 + half * 64 + wq4 * 16 + (lane >> 4)) * 64 + (cg & 6) * 8 + (lane & 15);
#pragma unroll
    for (int j = 0; j < 8; j++) {
      uint4 v;
      asm volatile("ld.shared.v4.u32 {%0, %1, %2, %3}, [%4];" : "=r"(v.x), "=r"(v.y), "=r"(v.z), "=r"(v.w) : "r"(stg + ((lane >> 3) & 1) * FST + (lane & 7) * 1024 + ((2 * j + (lane >> 4)) ^ (lane & 7)) * 16) : "memory");
      op[j * 128] = v;
    }
    if (tid == 256) EV(20);
  } else {
    asm volatile("setmaxnreg.inc.sync.aligned.u32 %0;" ::"n"(REG_ATT));
    constexpr uint32_t H128 = dhi(1024, 1);
    const uint32_t xl = dlo(sb + X_OFF + wg * 65536, 16);
    uint32_t qh[4][4], qb[4][4];
    float qn;
    {
      float d[32];
      zero(d);
      const uint32_t wl = dlo(sb + W_OFF, 8192);
#pragma unroll 1
      for (int s = 0; s < 4; s++) {
        mbar_wait(sb + B_WQ + 8 * s, 0);
        mbar_wait(sb + B_XFULL + 32 * wg + 8 * s, 0);
        wg_fence();
#pragma unroll
        for (int k = 0; k < 8; k++) mma_ss_t64(d, mk64(xl + (2 * s + (k >> 2)) * 512 + 2 * (k & 3), H128), mk64(wl + s * 1024 + 128 * k, H128), 1);
        wg_commit();
        wg_wait<0>();
        if (lane == 0) mbar_arrive(sb + B_WEMPTY + 8 * s);
      }
      pin(d);
      if (tid == 0) EV(44);
      uint32_t nm = 0;
#pragma unroll
      for (int h = 0; h < 4; h++) {
        const float* dh = d + 8 * h;
#pragma unroll
        for (int i = 0; i < 4; i++) {
          const float c = (i & 1) ? QS / 32.f : QS * 16.f;
          qh[h][i] = packh(dh[2 * i] * c, dh[2 * i + 1] * c);
          qb[h][i] = pack2(dh[2 * i], dh[2 * i + 1]);
        }
        float n0 = sq4(dh[0], dh[1], dh[4], dh[5]), n1 = sq4(dh[2], dh[3], dh[6], dh[7]);
        n0 += __shfl_xor_sync(~0u, n0, 1); n1 += __shfl_xor_sync(~0u, n1, 1);
        n0 += __shfl_xor_sync(~0u, n0, 2); n1 += __shfl_xor_sync(~0u, n1, 2);
        nm = max(nm, max(__float_as_uint(n0), __float_as_uint(n1)));
      }
      qn = __uint_as_float(nm) * (QS * QS);
    }
    if (tid == 0) EV(3);
    mbar_wait(sb + B_KVFULL, 0);
    if (tid == 0) { EV(5); EVC(0); }
    uint8_t* odst = a_tb + wg * A_BYTES + (224 + cg * 4) * 1024 + wq4 * 256 + lane * 4;
    const uint8_t* src = a_tb + half * A_BYTES + 256 * 1024 + warp * 4096 + lane * 16;
    uint32_t r[8][4];
    attn_passes(qh, qb, qn, odst, wg, r, src);
    mbar_wait(sb + B_TAIL, 0);
    const uint32_t dst = o_off(warp) + (lane >> 4) * 1024 + (lane & 15) * 16;
    uint32_t pend = 255;
#pragma unroll 1
    for (int i = 0; i < 0x100000; i++) {
#pragma unroll
      for (int j = 0; j < 8; j++) if (__all_sync(~0u, min(min(r[j][0], r[j][1]), min(r[j][2], r[j][3])) != 0)) {
        stsm4(dst + (j >> 2) * 2048 + (j & 3) * 256, ~r[j][0], ~r[j][1], ~r[j][2], ~r[j][3]);
        pend ^= 1u << j;
      }
      if (!pend) break;
#pragma unroll
      for (int j = 0; j < 8; j++) ld_rlx128(r[j], src + j * 512, pend & (1u << j));
    }
    o_push(warp, lane);
  }
}

typedef CUresult (*EncodeFn)(CUtensorMap*, CUtensorMapDataType, cuuint32_t, void*, const cuuint64_t*, const cuuint64_t*, const cuuint32_t*, const cuuint32_t*,
                             CUtensorMapInterleave, CUtensorMapSwizzle, CUtensorMapL2promotion, CUtensorMapFloatOOBfill);

void make_map(EncodeFn fn, CUtensorMap* m, const void* p, uint64_t cols, uint64_t rows, uint32_t bc, uint32_t br, CUtensorMapSwizzle sw) {
  cuuint64_t dims[2] = {cols, rows}, strides[1] = {cols * 2};
  cuuint32_t box[2] = {bc, br}, es[2] = {1, 1};
  fn(m, CU_TENSOR_MAP_DATA_TYPE_BFLOAT16, 2, const_cast<void*>(p), dims, strides, box, es, CU_TENSOR_MAP_INTERLEAVE_NONE, sw,
     CU_TENSOR_MAP_L2_PROMOTION_L2_128B, CU_TENSOR_MAP_FLOAT_OOB_FILL_NONE);
}

void make_map3(EncodeFn fn, CUtensorMap* m, const void* p, uint64_t bw, uint64_t nblk, uint64_t rows, uint32_t bc, uint32_t br, CUtensorMapSwizzle sw) {
  cuuint64_t dims[3] = {bw, rows, nblk}, strides[2] = {bw * nblk * 2, bw * 2};
  cuuint32_t box[3] = {bc, br, 2}, es[3] = {1, 1, 1};
  fn(m, CU_TENSOR_MAP_DATA_TYPE_BFLOAT16, 3, const_cast<void*>(p), dims, strides, box, es, CU_TENSOR_MAP_INTERLEAVE_NONE, sw,
     CU_TENSOR_MAP_L2_PROMOTION_L2_128B, CU_TENSOR_MAP_FLOAT_OOB_FILL_NONE);
}

void make_map4(EncodeFn fn, CUtensorMap* m, const void* p, uint64_t rows, uint64_t rg) {
  cuuint64_t dims[4] = {64, rg, rows / rg, 8}, strides[3] = {1024, rg * 1024, 128};
  cuuint32_t box[4] = {64, 32, 2, 2}, es[4] = {1, 1, 1, 1};
  fn(m, CU_TENSOR_MAP_DATA_TYPE_BFLOAT16, 4, const_cast<void*>(p), dims, strides, box, es, CU_TENSOR_MAP_INTERLEAVE_NONE, CU_TENSOR_MAP_SWIZZLE_128B,
     CU_TENSOR_MAP_L2_PROMOTION_L2_128B, CU_TENSOR_MAP_FLOAT_OOB_FILL_NONE);
}

}

extern "C" void kernel_launch(void* const* d_in, const int* in_sizes, int n_in, void* d_out, int out_size) {
  void* fp = nullptr;
  cudaDriverEntryPointQueryResult qr;
  cudaGetDriverEntryPoint("cuTensorMapEncodeTiled", &fp, cudaEnableDefault, &qr);
  EncodeFn fn = (EncodeFn)fp;
  Maps mp;
  make_map3(fn, &mp.x, d_in[0], 64, 8, S_, 64, 64, CU_TENSOR_MAP_SWIZZLE_128B);
  make_map(fn, &mp.wq, d_in[1], D_, D_, 64, 128, CU_TENSOR_MAP_SWIZZLE_128B);
  make_map4(fn, &mp.wo, d_in[4], D_, 64);
  make_map(fn, &mp.wg, d_in[6], F_, D_, 64, 64, CU_TENSOR_MAP_SWIZZLE_128B);
  make_map(fn, &mp.wu, d_in[7], F_, D_, 64, 64, CU_TENSOR_MAP_SWIZZLE_128B);
  make_map4(fn, &mp.wd, d_in[8], F_, 32);
  make_map(fn, &mp.wg2, d_in[6], F_, D_, 32, 128, CU_TENSOR_MAP_SWIZZLE_64B);
  make_map(fn, &mp.wu2, d_in[7], F_, D_, 32, 128, CU_TENSOR_MAP_SWIZZLE_64B);
  cudaFuncSetAttribute(fused_kernel, cudaFuncAttributeMaxDynamicSharedMemorySize, SMEM_BYTES);
  fused_kernel<<<132, 512, SMEM_BYTES, cudaStreamPerThread>>>(mp, (const uint16_t*)d_in[9], (const uint4*)d_in[2], (const uint4*)d_in[3], (const uint8_t*)d_in[8], (const uint8_t*)d_in[4], (uint4*)d_out);
}
```
